```python
import torch

def _softmax(x, axis=-1):
    return torch.softmax(x, dim=axis)
def _gelu(x):
    return torch.nn.functional.gelu(x, approximate="tanh")
def _silu(x):
    return torch.nn.functional.silu(x)
def _sigmoid(x):
    return torch.sigmoid(x)
def _layernorm(x, axis=-1, eps=1e-5):
    m = x.mean(dim=axis, keepdim=True)
    v = x.var(dim=axis, keepdim=True, unbiased=False)
    return (x - m) / torch.sqrt(v + eps)
def _scatter_add(tgt, idx, src, axis=0):
    return tgt.clone().index_add_(axis, idx, src)
def _segment_sum(src, seg, n):
    out = torch.zeros((n,) + src.shape[1:], dtype=src.dtype)
    return out.index_add_(0, seg, src)
def _pad(x, pw):
    flat = tuple(v for pair in reversed(pw) for v in pair)
    return torch.nn.functional.pad(x, flat)

kernel_name = 'parallel_sum__gqa_block_cached__geglu_ffn__decode'

def setup_inputs():

    _w = (lambda a: (lambda t: t.to(torch.bfloat16) if t.is_floating_point() else t)(torch.as_tensor(a)))
    def _A_setup():
        B, Sq, D = 2, 1, 1024
        Hq, Hkv, Sk, Dh = 32, 4, 32768, 128
        assert Hq % Hkv == 0, (Hq, Hkv)
        return {
            "x": _w((lambda *s: torch.randn(*s, dtype=torch.bfloat16) * 0.05)(B, Sq, D)),
            "k_cache": _w((lambda *s: torch.randn(*s, dtype=torch.bfloat16) * 3.2)(B, Hkv, Sk, Dh)),
            "v_cache": _w((lambda *s: torch.randn(*s, dtype=torch.bfloat16) * 1.6)(B, Hkv, Sk, Dh)),
            "wq": _w((lambda *s: torch.randn(*s, dtype=torch.bfloat16) * 3.2)(D, Hq * Dh) * (D ** -0.5)),
            "wo": _w((lambda *s: torch.randn(*s, dtype=torch.bfloat16) * 1.6)(Hq * Dh, D) * ((Hq * Dh) ** -0.5)),
        }
    _A_in = _A_setup()

    def _B_setup():
        B, S, D, F = 2, 1, 1024, 3584
        return {
            "x": _w((lambda *s: torch.randn(*s, dtype=torch.bfloat16) * 0.05)(B, S, D)),
            "w_gate": _w((lambda *s: torch.randn(*s, dtype=torch.bfloat16) * 0.05)(D, F)),
            "w_up": _w((lambda *s: torch.randn(*s, dtype=torch.bfloat16) * 0.05)(D, F)),
            "w_down": _w((lambda *s: torch.randn(*s, dtype=torch.bfloat16) * 0.05)(F, D)),
        }
    _B_in = _B_setup()

    return {
        "A_x": _A_in["x"],
        "A_k_cache": _A_in["k_cache"],
        "A_v_cache": _A_in["v_cache"],
        "A_wq": _A_in["wq"],
        "A_wo": _A_in["wo"],
        "B_x": _B_in["x"],
        "B_w_gate": _B_in["w_gate"],
        "B_w_up": _B_in["w_up"],
        "B_w_down": _B_in["w_down"],
    }

def reference(A_x, A_k_cache, A_v_cache, A_wq, A_wo, B_x, B_w_gate, B_w_up, B_w_down):
    def _A_ref(x, k_cache, v_cache, wq, wo):
        B, Sq, D = x.shape
        Hq, Dh = 32, 128
        Hkv = k_cache.shape[1]
        rep = Hq // Hkv
        q = (lambda x, *d: x.permute(*d))((x @ wq).reshape(B, Sq, Hq, Dh), 0, 2, 1, 3)
        k = (lambda x, n, axis: torch.repeat_interleave(x, n, dim=axis))(k_cache, rep, axis=1)
        v = (lambda x, n, axis: torch.repeat_interleave(x, n, dim=axis))(v_cache, rep, axis=1)
        scores = torch.einsum("bhqd,bhkd->bhqk", q, k) * (Dh ** -0.5)
        p = _softmax(scores, axis=-1)
        o = torch.einsum("bhqk,bhkd->bhqd", p, v)
        return (lambda x, *d: x.permute(*d))(o, 0, 2, 1, 3).reshape(B, Sq, Hq * Dh) @ wo

    def _B_ref(x, w_gate, w_up, w_down):
        return (_gelu(x @ w_gate) * (x @ w_up)) @ w_down

    x = A_x
    xn = _layernorm(x, axis=-1)
    return x + _A_ref(xn, A_k_cache, A_v_cache, A_wq, A_wo) + _B_ref(xn, B_w_gate, B_w_up, B_w_down)
```

```cpp
#include <cuda_runtime.h>
#include <cuda_bf16.h>
#include <cuda.h>
#include <stdint.h>

namespace {

constexpr int D_MODEL = 1024, SK = 32768, FF = 3584, QW = 4096;
constexpr int NCTA = 132;
constexpr int MEMBERS = 33;
constexpr int NSLOT = 6;
constexpr int SLOT = 16384;
constexpr int TILES_B = 512;
constexpr int TILES = 1024;
constexpr int REC = 136;
constexpr int GU_FIRST = 20;
#define WINDOW 3
#define T_WO_DEF 1024
#define T_WD_DEF 1024

#define T_THR_DEF 1024
#define DEPTH_DEF 1
#define PREW 1

constexpr int SM_RING = 0;
constexpr int SM_WO = NSLOT * SLOT;
constexpr int SM_WD = SM_WO + 65536;
constexpr int SM_Q = SM_WD + 57344;
constexpr int SM_H = SM_Q + 2 * 8 * 136 * 2;
constexpr int SM_O = SM_H + 2 * 136 * 2;
constexpr int SM_RED = SM_O + 2 * 136 * 2;
constexpr int SM_ML = SM_RED + 3 * 4 * 64 * 4;
constexpr int SM_META = SM_ML + 4 * 8 * 2 * 4;
constexpr int SM_BAR = SM_META + 32;
constexpr int BAR_FULL = SM_BAR, BAR_EMPTY = BAR_FULL + 8 * NSLOT, BAR_WO = BAR_EMPTY + 8 * NSLOT,
              BAR_WD = BAR_WO + 8 * 4;
constexpr int SM_TOTAL = BAR_WD + 8 * 7;
static_assert(SM_TOTAL <= 232448, "smem");

enum { NB_INIT = 0, NB_ATT = 1, NB_QPUB, NB_FLUSH0, NB_FLUSH1, NB_Q0, NB_Q1, NB_H, NB_AUX };

struct Params {
    CUtensorMap k, v, wq, wg, wu, wo, wd;
    const __nv_bfloat16* x;
    __nv_bfloat16* out;
    int t_wo, t_wd, t_thr, depth;
};

__device__ unsigned g_epoch;
__device__ unsigned g_ctr[4 * 32];
__device__ __align__(128) uint32_t g_q[2 * QW];
__device__ __align__(128) uint32_t g_h[2 * FF];
__device__ __align__(128) uint32_t g_part[2 * 32 * MEMBERS * REC];
__device__ __align__(128) uint32_t g_fin[4 * 64 * 512];

#define STAMP(cond, i)

constexpr uint32_t SPIN_MAX = 1u << 20;

__device__ __forceinline__ bool elect_one() {
    uint32_t p;
    asm volatile("{\n.reg .pred p;\nelect.sync _|p, 0xffffffff;\nselp.u32 %0, 1, 0, p;\n}" : "=r"(p));
    return p;
}
__device__ __forceinline__ uint32_t claim(unsigned* ctr) {
    uint32_t v;
    asm volatile("atom.relaxed.gpu.global.add.u32 %0, [%1], 1;" : "=r"(v) : "l"(ctr) : "memory");
    return v;
}

__device__ __forceinline__ void mbar_init(uint32_t b, int c) {
    asm volatile("mbarrier.init.shared::cta.b64 [%0], %1;" ::"r"(b), "r"(c) : "memory");
}
__device__ __forceinline__ void mbar_expect(uint32_t b, uint32_t bytes) {
    asm volatile("mbarrier.arrive.expect_tx.shared::cta.b64 _, [%0], %1;" ::"r"(b), "r"(bytes) : "memory");
}
__device__ __forceinline__ void mbar_arrive(uint32_t b) {
    asm volatile("mbarrier.arrive.shared::cta.b64 _, [%0];" ::"r"(b) : "memory");
}
__device__ __forceinline__ void mbar_wait(uint32_t b, uint32_t ph) {
    asm volatile(
        "{\n.reg .pred p;\n.reg .u32 n;\nmov.u32 n, 0;\n"
        "WAIT:\nmbarrier.try_wait.parity.shared::cta.b64 p, [%0], %1;\n@p bra DONE;\n"
        "add.u32 n, n, 1;\nsetp.lt.u32 p, n, 0x100000;\n@p bra WAIT;\ntrap;\nDONE:\n}" ::"r"(b), "r"(ph) : "memory");
}
__device__ __forceinline__ void tma3(uint32_t dst, const CUtensorMap* m, int c0, int c1, int c2, uint32_t bar,
                                     uint64_t pol) {
    asm volatile(
        "cp.async.bulk.tensor.3d.shared::cluster.global.mbarrier::complete_tx::bytes.L2::cache_hint "
        "[%0], [%1, {%3,%4,%5}], [%2], %6;" ::"r"(dst), "l"(m), "r"(bar), "r"(c0), "r"(c1), "r"(c2), "l"(pol)
        : "memory");
}
__device__ __forceinline__ void bar_sync(int id, int n) { asm volatile("bar.sync %0, %1;" ::"r"(id), "r"(n) : "memory"); }
__device__ __forceinline__ void bar_arrive(int id, int n) { asm volatile("bar.arrive %0, %1;" ::"r"(id), "r"(n) : "memory"); }

__device__ __forceinline__ void ldsm4(uint32_t a, uint32_t (&r)[4]) {
    asm volatile("ldmatrix.sync.aligned.m8n8.x4.shared.b16 {%0,%1,%2,%3}, [%4];"
                 : "=r"(r[0]), "=r"(r[1]), "=r"(r[2]), "=r"(r[3]) : "r"(a) : "memory");
}
__device__ __forceinline__ void ldsm4t(uint32_t a, uint32_t (&r)[4]) {
    asm volatile("ldmatrix.sync.aligned.m8n8.x4.trans.shared.b16 {%0,%1,%2,%3}, [%4];"
                 : "=r"(r[0]), "=r"(r[1]), "=r"(r[2]), "=r"(r[3]) : "r"(a) : "memory");
}
__device__ __forceinline__ void mma(float (&c)[4], const uint32_t (&a)[4], uint32_t b0, uint32_t b1) {
    asm volatile("mma.sync.aligned.m16n8k16.row.col.f32.bf16.bf16.f32 {%0,%1,%2,%3}, {%4,%5,%6,%7}, {%8,%9}, {%0,%1,%2,%3};"
                 : "+f"(c[0]), "+f"(c[1]), "+f"(c[2]), "+f"(c[3])
                 : "r"(a[0]), "r"(a[1]), "r"(a[2]), "r"(a[3]), "r"(b0), "r"(b1));
}
__device__ __forceinline__ uint32_t movm(uint32_t a) {
    uint32_t d;
    asm volatile("movmatrix.sync.aligned.m8n8.trans.b16 %0, %1;" : "=r"(d) : "r"(a));
    return d;
}
__device__ __forceinline__ uint32_t pack_bf16(float lo, float hi) {
    uint32_t d;
    asm("cvt.rn.bf16x2.f32 %0, %1, %2;" : "=r"(d) : "f"(hi), "f"(lo));
    return d;
}
__device__ __forceinline__ float bf_lo(uint32_t v) { return __uint_as_float(v << 16); }
__device__ __forceinline__ float bf_hi(uint32_t v) { return __uint_as_float(v & 0xffff0000u); }
__device__ __forceinline__ float rbf(float x) { return __bfloat162float(__float2bfloat16_rn(x)); }
__device__ __forceinline__ float expd(float x) {
    float y;
    asm("ex2.approx.ftz.f32 %0, %1;" : "=f"(y) : "f"(x * 1.4426950408889634f));
    return y;
}
__device__ __forceinline__ uint32_t lds32(uint32_t a) {
    uint32_t v;
    asm volatile("ld.shared.u32 %0, [%1];" : "=r"(v) : "r"(a) : "memory");
    return v;
}
__device__ __forceinline__ float4 lds128f(uint32_t a) {
    float4 v;
    asm volatile("ld.shared.v4.f32 {%0,%1,%2,%3}, [%4];" : "=f"(v.x), "=f"(v.y), "=f"(v.z), "=f"(v.w) : "r"(a) : "memory");
    return v;
}
__device__ __forceinline__ void sts32(uint32_t a, uint32_t v) { asm volatile("st.shared.u32 [%0], %1;" ::"r"(a), "r"(v) : "memory"); }
__device__ __forceinline__ void sts32f(uint32_t a, float v) { asm volatile("st.shared.f32 [%0], %1;" ::"r"(a), "f"(v) : "memory"); }
__device__ __forceinline__ void sts64(uint32_t a, uint32_t x, uint32_t y) {
    asm volatile("st.shared.v2.u32 [%0], {%1,%2};" ::"r"(a), "r"(x), "r"(y) : "memory");
}
__device__ __forceinline__ uint32_t ldg_rlx(const uint32_t* p) {
    uint32_t v;
    asm volatile("ld.relaxed.gpu.global.u32 %0, [%1];" : "=r"(v) : "l"(p) : "memory");
    return v;
}
__device__ __forceinline__ uint2 ldg_rlx2(const uint32_t* p) {
    uint2 v;
    asm volatile("ld.relaxed.gpu.global.v2.u32 {%0,%1}, [%2];" : "=r"(v.x), "=r"(v.y) : "l"(p) : "memory");
    return v;
}
__device__ __forceinline__ uint4 ldg_rlx4(const uint32_t* p) {
    uint4 v;
    asm volatile("ld.relaxed.gpu.global.v4.u32 {%0,%1,%2,%3}, [%4];" : "=r"(v.x), "=r"(v.y), "=r"(v.z), "=r"(v.w) : "l"(p) : "memory");
    return v;
}
__device__ __forceinline__ void stg_rlx(uint32_t* p, uint32_t v) {
    asm volatile("st.relaxed.gpu.global.u32 [%0], %1;" ::"l"(p), "r"(v) : "memory");
}
__device__ __forceinline__ void stg_rlx2(uint32_t* p, uint32_t x, uint32_t y) {
    asm volatile("st.relaxed.gpu.global.v2.u32 [%0], {%1,%2};" ::"l"(p), "r"(x), "r"(y) : "memory");
}
__device__ __forceinline__ void stg_rlx4(uint32_t* p, uint32_t x, uint32_t y, uint32_t z, uint32_t w) {
    asm volatile("st.relaxed.gpu.global.v4.u32 [%0], {%1,%2,%3,%4};" ::"l"(p), "r"(x), "r"(y), "r"(z), "r"(w) : "memory");
}
__device__ __forceinline__ uint32_t tagf(float v, uint32_t tag) { return (__float_as_uint(v) & ~0xFu) | tag; }
__device__ __forceinline__ float untag(uint32_t w) { return __uint_as_float(w & ~0xFu); }
__device__ __forceinline__ bool ok4(const uint4& v, uint32_t tag) {
    return ((((v.x ^ tag) | (v.y ^ tag)) | ((v.z ^ tag) | (v.w ^ tag))) & 0xFu) == 0;
}
__device__ __forceinline__ uint32_t pack_hi(uint32_t a, uint32_t b) { return __byte_perm(a, b, 0x7632); }

__device__ __forceinline__ uint32_t* fin_slot(int c, int role, int w, int lane) {
    return g_fin + ((c & 3) * 32 + w * 8 + (lane & 3) * 2) * 1024 + (role * 32 + (c >> 2)) * 16 + (lane >> 2) * 2;
}

template <int NBOX, int KSB>
__device__ __forceinline__ void tail_gemv(uint32_t wbase, uint32_t bar0, uint32_t vec, uint32_t* dst, int w, int lane,
                                          uint32_t tag) {
    const int g = lane >> 2, t = lane & 3;
    const int j = lane >> 3, r = lane & 7;
    float acc[4][4];
#pragma unroll
    for (int i = 0; i < 4; i++) acc[i][0] = acc[i][1] = acc[i][2] = acc[i][3] = 0.f;
    const uint32_t vb = vec + (g & 1) * 272 + t * 4;
    const uint32_t rowoff = w * (KSB * 16 * 128) + ((j >> 1) * 8 + r) * 128;
#pragma unroll 1
    for (int bx = 0; bx < NBOX; bx++) {
        mbar_wait(bar0 + bx * 8, 0);
#pragma unroll
        for (int ks = 0; ks < KSB; ks++) {
            const uint32_t b0 = lds32(vb + (bx * KSB + ks) * 32), b1 = lds32(vb + (bx * KSB + ks) * 32 + 16);
#pragma unroll
            for (int mt = 0; mt < 4; mt++) {
                uint32_t a[4];
                ldsm4t(wbase + bx * (KSB * 8192) + rowoff + ks * 2048 + (((2 * mt + (j & 1)) ^ r) << 4), a);
                mma(acc[mt], a, b0, b1);
            }
        }
    }
    float v0 = acc[0][0], v1 = acc[0][1], v2 = acc[0][2], v3 = acc[0][3];
#pragma unroll
    for (int i = 1; i < 4; i++)
        if (t == i) { v0 = acc[i][0]; v1 = acc[i][1]; v2 = acc[i][2]; v3 = acc[i][3]; }
    stg_rlx2(dst, tagf(v0, tag), tagf(v1, tag));
    stg_rlx2(dst + 1024, tagf(v2, tag), tagf(v3, tag));
}

__global__ void __launch_bounds__(288, 1) fused_decode_kernel(const __grid_constant__ Params P) {
    extern __shared__ __align__(1024) unsigned char smem_raw[];
    const uint32_t sm = (uint32_t)__cvta_generic_to_shared(smem_raw);
    const int c = blockIdx.x;
    const int warp = threadIdx.x >> 5, lane = threadIdx.x & 31;
    const int kvh = c & 3, member = c >> 2;
    const bool has_q = c < 128, has_gu = c >= GU_FIRST, has_fin = c < 128;

    if (warp == 8) {
        uint32_t win[WINDOW];
        uint64_t pol;
        uint32_t t = 0, epoch = 0;
        constexpr int FIRST = WINDOW < 4 ? WINDOW : 4;
        asm volatile("createpolicy.fractional.L2::evict_first.b64 %0, 1.0;" : "=l"(pol));
        if (elect_one()) {
            STAMP(true, 0);
#pragma unroll
            for (int i = 0; i < FIRST; i++) mbar_init(sm + BAR_FULL + i * 8, 1);
            asm volatile("fence.mbarrier_init.release.cluster;" ::: "memory");
            const CUtensorMap* m0 = has_q ? &P.wq : &P.wg;
            const CUtensorMap* m1 = has_q ? &P.wq : &P.wu;
            const int c0 = has_q ? c * 32 : (c - GU_FIRST) * 32;
#pragma unroll
            for (int i = 0; i < FIRST; i++) {
                mbar_expect(sm + BAR_FULL + i * 8, SLOT);
                tma3(sm + i * SLOT, (i & 1) ? m1 : m0, c0, (has_q ? i : i >> 1) * 256, 0, sm + BAR_FULL + i * 8, pol);
            }
            STAMP(true, 1);
#pragma unroll
            for (int i = FIRST; i < 2 * NSLOT + 11; i++) mbar_init(sm + SM_BAR + i * 8, (i >= NSLOT && i < 2 * NSLOT) ? 4 : 1);
            asm volatile("fence.mbarrier_init.release.cluster;" ::: "memory");
        }
        __syncwarp();
        bar_arrive(NB_INIT, 288);
        if (elect_one()) {
            t = claim(&g_ctr[kvh * 32]);
            epoch = ldg_rlx(&g_epoch);
            asm volatile("prefetch.tensormap [%0];" ::"l"(&P.wg) : "memory");
            asm volatile("prefetch.tensormap [%0];" ::"l"(&P.wu) : "memory");
            asm volatile("prefetch.tensormap [%0];" ::"l"(&P.k) : "memory");
            asm volatile("prefetch.tensormap [%0];" ::"l"(&P.v) : "memory");
            asm volatile("prefetch.tensormap [%0];" ::"l"(&P.wo) : "memory");
            asm volatile("prefetch.tensormap [%0];" ::"l"(&P.wd) : "memory");
#pragma unroll
            for (int i = 0; i < WINDOW; i++) win[i] = (i >= WINDOW - FIRST) ? sm + BAR_FULL + (i - (WINDOW - FIRST)) * 8 : 0;
            int slot = FIRST;
            uint32_t sph = 0;
            int depth = 0;
            auto throttle = [&](uint32_t entry) {
                uint32_t e = win[0];
#pragma unroll
                for (int i = 1; i < WINDOW; i++) e = depth == i ? win[i] : e;
                if (e) mbar_wait(e & ~1u, e & 1u);
#pragma unroll
                for (int i = 0; i + 1 < WINDOW; i++) win[i] = win[i + 1];
                win[WINDOW - 1] = entry;
            };
            auto advance = [&]() { if (++slot == NSLOT) { slot = 0; sph ^= 1; } };
            auto ring_load = [&](const CUtensorMap* m, int c0, int c1, int meta) {
                const uint32_t fb = sm + BAR_FULL + slot * 8;
                throttle(fb | sph);
                mbar_wait(sm + BAR_EMPTY + slot * 8, sph ^ 1);
                sts32(sm + SM_META + slot * 4, meta);
                mbar_expect(fb, SLOT);
                tma3(sm + slot * SLOT, m, c0, c1, 0, fb, pol);
                advance();
            };
            auto flush_mark = [&]() {
                mbar_wait(sm + BAR_EMPTY + slot * 8, sph ^ 1);
                sts32(sm + SM_META + slot * 4, 1);
                mbar_arrive(sm + BAR_FULL + slot * 8);
                advance();
            };
            const int cb = c & 3, ksp = c >> 2;
            auto load_wo = [&]() {
#pragma unroll 1
                for (int i = 0; i < 4; i++) {
                    const uint32_t fb = sm + BAR_WO + i * 8;
                    throttle(fb);
                    mbar_expect(fb, 16384);
                    tma3(sm + SM_WO + i * 16384, &P.wo, 0, ksp * 128 + i * 32, cb * 4, fb, pol);
                }
            };
            auto load_wd = [&]() {
#pragma unroll 1
                for (int i = 0; i < 7; i++) {
                    const uint32_t fb = sm + BAR_WD + i * 8;
                    if (!(i & 1)) throttle(i < 6 ? fb + 8 : fb);
                    mbar_expect(fb, 8192);
                    tma3(sm + SM_WD + i * 8192, &P.wd, 0, ksp * 112 + i * 16, cb * 4, fb, pol);
                }
            };
            const int n1 = (has_q ? 4 : 0) + (has_gu ? 8 : 0);
#pragma unroll 1
            for (int i = FIRST; i < n1; i++) {
                if (has_q && i < 4) ring_load(&P.wq, c * 32, i * 256, 0);
                else {
                    const int u = i - (has_q ? 4 : 0);
                    ring_load((u & 1) ? &P.wu : &P.wg, (c - GU_FIRST) * 32, (u >> 1) * 256, 0);
                }
            }
            STAMP(true, 2);
            sts32(sm + SM_META + 7 * 4, epoch);
            bool b1 = false, wo_done = !has_fin, wd_done = !has_fin;
#pragma unroll 1
            while (t < TILES) {
                const uint32_t tn = claim(&g_ctr[kvh * 32]);
                if ((int)t >= P.t_thr) depth = P.depth;
                if (t >= TILES_B && !b1) { flush_mark(); b1 = true; }
                if (!wo_done && (int)t >= P.t_wo) { load_wo(); wo_done = true; }
                if (!wd_done && (int)t >= P.t_wd) { load_wd(); wd_done = true; }
                const int row = ((t >> 9) * 4 + kvh) * SK + (t & (TILES_B - 1)) * 64;
                ring_load(&P.k, 0, row, 0);
                ring_load(&P.v, 0, row, 0);
                t = tn;
            }
            STAMP(true, 3);
            depth = P.depth;
            if (!b1) flush_mark();
            flush_mark();
            if (!wo_done) load_wo();
            if (!wd_done) load_wd();
            STAMP(true, 4);
        }
        if (!has_fin) return;
        __syncwarp();
        epoch = lds32(sm + SM_META + 7 * 4);
        const uint32_t tag = epoch % 15u + 1u;
        const int cb = c & 3, ksp = c >> 2;
        const int i8 = lane >> 2, j4 = lane & 3;
        const int col = cb * 256 + ksp * 8 + j4 * 2;
        const uint32_t x0 = *reinterpret_cast<const uint32_t*>(P.x + col);
        const uint32_t x1 = *reinterpret_cast<const uint32_t*>(P.x + D_MODEL + col);
        mbar_wait(sm + BAR_WD + 6 * 8, 0);
        mbar_wait(sm + BAR_WO + 3 * 8, 0);
        STAMP(lane == 0, 5);
        const uint32_t* src = g_fin + (cb * 32 + ksp) * 1024 + lane * 4;
        uint4 v[8];
        uint32_t pend = 0xFF, spins = 0;
        while (true) {
#pragma unroll
            for (int n = 0; n < 8; n++)
                if (pend >> n & 1) v[n] = ldg_rlx4(src + n * 128);
#pragma unroll
            for (int n = 0; n < 8; n++)
                if (ok4(v[n], tag)) pend &= ~(1u << n);
            if (__all_sync(~0u, pend == 0)) break;
            if (++spins > SPIN_MAX) __trap();
        }
        float a[4], f[4];
        a[0] = (untag(v[0].x) + untag(v[1].x)) + (untag(v[2].x) + untag(v[3].x));
        a[1] = (untag(v[0].y) + untag(v[1].y)) + (untag(v[2].y) + untag(v[3].y));
        a[2] = (untag(v[0].z) + untag(v[1].z)) + (untag(v[2].z) + untag(v[3].z));
        a[3] = (untag(v[0].w) + untag(v[1].w)) + (untag(v[2].w) + untag(v[3].w));
        f[0] = (untag(v[4].x) + untag(v[5].x)) + (untag(v[6].x) + untag(v[7].x));
        f[1] = (untag(v[4].y) + untag(v[5].y)) + (untag(v[6].y) + untag(v[7].y));
        f[2] = (untag(v[4].z) + untag(v[5].z)) + (untag(v[6].z) + untag(v[7].z));
        f[3] = (untag(v[4].w) + untag(v[5].w)) + (untag(v[6].w) + untag(v[7].w));
#pragma unroll
        for (int s = 4; s < 32; s <<= 1) {
#pragma unroll
            for (int e = 0; e < 4; e++) {
                a[e] += __shfl_xor_sync(~0u, a[e], s);
                f[e] += __shfl_xor_sync(~0u, f[e], s);
            }
        }
        if (i8 < 2) {
            const uint32_t xv = i8 ? x1 : x0;
            const float al = i8 ? a[1] : a[0], ah = i8 ? a[3] : a[2];
            const float fl = i8 ? f[1] : f[0], fh = i8 ? f[3] : f[2];
            const float lo = rbf(bf_lo(xv) + rbf(al)) + rbf(fl);
            const float hi = rbf(bf_hi(xv) + rbf(ah)) + rbf(fh);
            *reinterpret_cast<uint32_t*>(P.out + i8 * D_MODEL + col) = pack_bf16(lo, hi);
        }
        if (c == 0 && lane < 4) {
            g_ctr[lane * 32] = 0;
            if (lane == 0) g_epoch = epoch + 1;
        }
        STAMP(lane == 0, 6);
    } else if (warp < 4) {
        const int w = warp;
        const int g = lane >> 2, t = lane & 3;
        const int j = lane >> 3, r = lane & 7;
        const uint32_t tag = ldg_rlx(&g_epoch) % 15u + 1u;
        if (PREW && has_q && w < 2) stg_rlx(g_q + w * QW + c * 32 + lane, 0);
        uint32_t xf[4][2];
        {
            const uint4* xv = reinterpret_cast<const uint4*>(P.x);
            uint4 u[2][4];
#pragma unroll
            for (int b = 0; b < 2; b++)
#pragma unroll
                for (int i = 0; i < 4; i++) u[b][i] = __ldg(xv + b * 128 + i * 32 + lane);
            const uint32_t* xe = reinterpret_cast<const uint32_t*>(P.x + (g & 1) * D_MODEL + (g >> 1) * 256 + w * 64 + 2 * t);
#pragma unroll
            for (int ks = 0; ks < 4; ks++) { xf[ks][0] = __ldg(xe + ks * 8); xf[ks][1] = __ldg(xe + ks * 8 + 4); }
            float mean[2], var[2];
#pragma unroll
            for (int b = 0; b < 2; b++) {
                float s = 0.f;
#pragma unroll
                for (int i = 0; i < 4; i++)
                    s += ((bf_lo(u[b][i].x) + bf_hi(u[b][i].x)) + (bf_lo(u[b][i].y) + bf_hi(u[b][i].y))) +
                         ((bf_lo(u[b][i].z) + bf_hi(u[b][i].z)) + (bf_lo(u[b][i].w) + bf_hi(u[b][i].w)));
#pragma unroll
                for (int o = 16; o; o >>= 1) s += __shfl_xor_sync(~0u, s, o);
                mean[b] = s * (1.f / D_MODEL);
                float q = 0.f;
#pragma unroll
                for (int i = 0; i < 4; i++) {
                    const uint32_t e[4] = {u[b][i].x, u[b][i].y, u[b][i].z, u[b][i].w};
#pragma unroll
                    for (int k = 0; k < 4; k++) {
                        const float d0 = bf_lo(e[k]) - mean[b], d1 = bf_hi(e[k]) - mean[b];
                        q = fmaf(d0, d0, q);
                        q = fmaf(d1, d1, q);
                    }
                }
#pragma unroll
                for (int o = 16; o; o >>= 1) q += __shfl_xor_sync(~0u, q, o);
                var[b] = q * (1.f / D_MODEL);
            }
            const float mu = rbf((g & 1) ? mean[1] : mean[0]);
            const float rs = 1.f / rbf(sqrtf(rbf(rbf((g & 1) ? var[1] : var[0]) + 1e-5f)));
#pragma unroll
            for (int ks = 0; ks < 4; ks++)
#pragma unroll
                for (int h = 0; h < 2; h++)
                    xf[ks][h] = pack_bf16(rbf(bf_lo(xf[ks][h]) - mu) * rs, rbf(bf_hi(xf[ks][h]) - mu) * rs);
        }
        bar_sync(NB_INIT, 288);
        STAMP(threadIdx.x == 0, 8);
        int slot = 0;
        uint32_t sph = 0;
        auto advance = [&]() { if (++slot == NSLOT) { slot = 0; sph ^= 1; } };
        auto release = [&]() {
            __syncwarp();
            if (lane == 0) mbar_arrive(sm + BAR_EMPTY + slot * 8);
            advance();
        };
        const uint32_t p1off = (w * 64 + (j >> 1) * 8 + r) * 64;
        auto p1_box = [&](float (&acc)[2][4], int rb) {
            mbar_wait(sm + BAR_FULL + slot * 8, sph);
            const bool live = (g >> 1) == rb;
#pragma unroll
            for (int ks = 0; ks < 4; ks++) {
                const uint32_t b0 = live ? xf[ks][0] : 0u, b1 = live ? xf[ks][1] : 0u;
#pragma unroll
                for (int mt = 0; mt < 2; mt++) {
                    uint32_t a[4];
                    ldsm4t(sm + slot * SLOT + p1off + ks * 1024 + (((2 * mt + (j & 1)) ^ (r >> 1)) << 4), a);
                    mma(acc[mt], a, b0, b1);
                }
            }
            release();
        };
        auto p1_store = [&](float (&acc)[2][4], int unit) {
#pragma unroll
            for (int mt = 0; mt < 2; mt++)
#pragma unroll
                for (int e = 0; e < 4; e++) {
                    float v = acc[mt][e];
                    v += __shfl_xor_sync(~0u, v, 1);
                    v += __shfl_xor_sync(~0u, v, 2);
                    if (t == 0) sts32f(sm + SM_RED + ((unit * 4 + w) * 64 + (e & 1) * 32 + mt * 16 + (e >> 1) * 8 + g) * 4, v);
                }
        };
        auto p1_sum = [&](int unit, int i) {
            const uint32_t a = sm + SM_RED + (unit * 256 + i) * 4;
            return (__uint_as_float(lds32(a)) + __uint_as_float(lds32(a + 256))) +
                   (__uint_as_float(lds32(a + 512)) + __uint_as_float(lds32(a + 768)));
        };
        if (has_q) {
            float acc[2][4] = {};
#pragma unroll 1
            for (int rb = 0; rb < 4; rb++) p1_box(acc, rb);
            p1_store(acc, 0);
            bar_sync(NB_ATT, 128);
            if (w < 2) stg_rlx(g_q + w * QW + c * 32 + lane, __float_as_uint(rbf(p1_sum(0, w * 32 + lane))) | tag);
            bar_arrive(NB_QPUB, 256);
            STAMP(threadIdx.x == 0, 9);
        }
        if (has_gu) {
            float ag[2][4] = {}, au[2][4] = {};
#pragma unroll 1
            for (int rb = 0; rb < 4; rb++) {
                p1_box(ag, rb);
                p1_box(au, rb);
                if (!has_q && rb == 1) bar_arrive(NB_QPUB, 256);
            }
            p1_store(ag, 1);
            p1_store(au, 2);
            bar_sync(NB_ATT, 128);
            if (w < 2) {
                const float gt = rbf(p1_sum(1, w * 32 + lane)), up = rbf(p1_sum(2, w * 32 + lane));
                const float in = 0.7978845608028654f * (gt + 0.044715f * gt * gt * gt);
                const float ge = rbf(0.5f * gt * (1.f + tanhf(in)));
                stg_rlx(g_h + w * FF + (c - GU_FIRST) * 32 + lane, __float_as_uint(rbf(ge * up)) | tag);
            }
        }
        STAMP(threadIdx.x == 0, 10);
        const uint32_t koff = (w * 16 + (j & 1) * 8 + r) * 128;
        const uint32_t voff = (w * 16 + (j >> 1) * 8 + r) * 128;
#pragma unroll 1
        for (int b = 0; b < 2; b++) {
            bar_sync(b ? NB_Q1 : NB_Q0, 256);
            STAMP(threadIdx.x == 0, 11 + b);
            uint32_t qf[8][2];
#pragma unroll
            for (int ks = 0; ks < 8; ks++) {
                const uint32_t a = sm + SM_Q + (b * 8 + g) * 272 + ks * 32 + t * 4;
                qf[ks][0] = lds32(a);
                qf[ks][1] = lds32(a + 16);
            }
            float o[8][4];
#pragma unroll
            for (int i = 0; i < 8; i++) o[i][0] = o[i][1] = o[i][2] = o[i][3] = 0.f;
            float m0 = __uint_as_float(0xF1490000u), m1 = m0, l0 = 0.f, l1 = 0.f;
#pragma unroll 1
            while (true) {
                mbar_wait(sm + BAR_FULL + slot * 8, sph);
                if (lds32(sm + SM_META + slot * 4)) break;
                float sa[4] = {0.f, 0.f, 0.f, 0.f}, sb[4] = {0.f, 0.f, 0.f, 0.f};
                const uint32_t kb = sm + slot * SLOT + koff;
#pragma unroll
                for (int ks = 0; ks < 4; ks++) {
                    uint32_t a0[4], a1[4];
                    const uint32_t sw = ((2 * ks + (j >> 1)) ^ r) << 4;
                    ldsm4(kb + sw, a0);
                    ldsm4(kb + 8192 + sw, a1);
                    mma(sa, a0, qf[ks][0], qf[ks][1]);
                    mma(sb, a1, qf[ks + 4][0], qf[ks + 4][1]);
                }
                release();
                float s[4];
                {
                    const uint32_t p01 = pack_bf16(sa[0] + sb[0], sa[1] + sb[1]), p23 = pack_bf16(sa[2] + sb[2], sa[3] + sb[3]);
                    const float sc = 0.08838834764831845f;
                    const uint32_t q01 = pack_bf16(bf_lo(p01) * sc, bf_hi(p01) * sc), q23 = pack_bf16(bf_lo(p23) * sc, bf_hi(p23) * sc);
                    s[0] = bf_lo(q01); s[1] = bf_hi(q01); s[2] = bf_lo(q23); s[3] = bf_hi(q23);
                }
                float x0 = fmaxf(s[0], s[2]), x1 = fmaxf(s[1], s[3]);
                if (__any_sync(~0u, x0 > m0 || x1 > m1)) {
#pragma unroll
                    for (int sft = 4; sft < 32; sft <<= 1) {
                        x0 = fmaxf(x0, __shfl_xor_sync(~0u, x0, sft));
                        x1 = fmaxf(x1, __shfl_xor_sync(~0u, x1, sft));
                    }
                    x0 = fmaxf(x0, m0);
                    x1 = fmaxf(x1, m1);
                    const float r0 = expd(m0 - x0), r1 = expd(m1 - x1);
                    m0 = x0; m1 = x1;
                    l0 *= r0; l1 *= r1;
#pragma unroll
                    for (int i = 0; i < 8; i++) { o[i][0] *= r0; o[i][1] *= r1; o[i][2] *= r0; o[i][3] *= r1; }
                }
                const float p0 = expd(s[0] - m0), p1 = expd(s[1] - m1), p2 = expd(s[2] - m0), p3 = expd(s[3] - m1);
                l0 += p0 + p2;
                l1 += p1 + p3;
                const uint32_t pb0 = movm(pack_bf16(p0, p1)), pb1 = movm(pack_bf16(p2, p3));
                mbar_wait(sm + BAR_FULL + slot * 8, sph);
                const uint32_t vb = sm + slot * SLOT + voff;
#pragma unroll
                for (int mt = 0; mt < 4; mt++) {
                    uint32_t a0[4], a1[4];
                    const uint32_t sw = ((2 * mt + (j & 1)) ^ r) << 4;
                    ldsm4t(vb + sw, a0);
                    ldsm4t(vb + 8192 + sw, a1);
                    mma(o[mt], a0, pb0, pb1);
                    mma(o[mt + 4], a1, pb0, pb1);
                }
                release();
            }
            STAMP(threadIdx.x == 0, 13 + 2 * b);
#pragma unroll
            for (int sft = 4; sft < 32; sft <<= 1) {
                l0 += __shfl_xor_sync(~0u, l0, sft);
                l1 += __shfl_xor_sync(~0u, l1, sft);
            }
            const uint32_t mb = sm + slot * SLOT;
            if (g == 0) {
                sts64(sm + SM_ML + (w * 8 + 2 * t) * 8, __float_as_uint(m0), __float_as_uint(l0));
                sts64(sm + SM_ML + (w * 8 + 2 * t + 1) * 8, __float_as_uint(m1), __float_as_uint(l1));
            }
#pragma unroll
            for (int mt = 0; mt < 8; mt++)
#pragma unroll
                for (int e = 0; e < 4; e++) {
                    const int d = mt * 16 + (e >> 1) * 8 + g, hd = 2 * t + (e & 1);
                    sts32f(mb + w * 4096 + hd * 512 + ((d * 4) ^ (t << 5)), o[mt][e]);
                }
            bar_sync(NB_ATT, 128);
            {
                const int hd = threadIdx.x >> 4, ch = threadIdx.x & 15;
                float mw[4], lw[4];
#pragma unroll
                for (int i = 0; i < 4; i++) {
                    mw[i] = __uint_as_float(lds32(sm + SM_ML + (i * 8 + hd) * 8));
                    lw[i] = __uint_as_float(lds32(sm + SM_ML + (i * 8 + hd) * 8 + 4));
                }
                const float M = fmaxf(fmaxf(mw[0], mw[1]), fmaxf(mw[2], mw[3]));
                float L = 0.f;
                float4 s0 = {0.f, 0.f, 0.f, 0.f}, s1 = s0;
#pragma unroll
                for (int i = 0; i < 4; i++) {
                    const float e = expd(mw[i] - M);
                    L = fmaf(e, lw[i], L);
                    const uint32_t a = mb + i * 4096 + hd * 512;
                    const float4 u0 = lds128f(a + ((ch * 16) ^ ((hd >> 1) << 5)));
                    const float4 u1 = lds128f(a + ((ch * 16 + 256) ^ ((hd >> 1) << 5)));
                    s0.x = fmaf(e, u0.x, s0.x); s0.y = fmaf(e, u0.y, s0.y); s0.z = fmaf(e, u0.z, s0.z); s0.w = fmaf(e, u0.w, s0.w);
                    s1.x = fmaf(e, u1.x, s1.x); s1.y = fmaf(e, u1.y, s1.y); s1.z = fmaf(e, u1.z, s1.z); s1.w = fmaf(e, u1.w, s1.w);
                }
                uint32_t* rec = g_part + ((b * 32 + kvh * 8 + hd) * MEMBERS + member) * REC;
                stg_rlx4(rec + ch * 4, tagf(s0.x, tag), tagf(s0.y, tag), tagf(s0.z, tag), tagf(s0.w, tag));
                stg_rlx4(rec + 64 + ch * 4, tagf(s1.x, tag), tagf(s1.y, tag), tagf(s1.z, tag), tagf(s1.w, tag));
                if (ch < 2) stg_rlx4(rec + 128 + ch * 4, tagf(M, tag), tagf(L, tag), tag, tag);
                if (PREW && b == 0) {
                    rec += 32 * MEMBERS * REC;
                    stg_rlx4(rec + ch * 4, 0, 0, 0, 0);
                    stg_rlx4(rec + 64 + ch * 4, 0, 0, 0, 0);
                    if (ch < 2) stg_rlx4(rec + 128 + ch * 4, 0, 0, 0, 0);
                    if (has_fin) {
                        uint32_t* const fin = fin_slot(c, 1, w, lane);
                        stg_rlx2(fin, 0, 0);
                        stg_rlx2(fin + 1024, 0, 0);
                    }
                }
            }
            if (has_fin) bar_arrive(b ? NB_FLUSH1 : NB_FLUSH0, 256);
            STAMP(threadIdx.x == 0, 14 + 2 * b);
            asm volatile("fence.proxy.async.shared::cta;" ::: "memory");
            release();
        }
        if (!has_fin) return;
        bar_sync(NB_H, 256);
        tail_gemv<7, 1>(sm + SM_WD, sm + BAR_WD, sm + SM_H, fin_slot(c, 1, w, lane), w, lane, tag);
        STAMP(threadIdx.x == 0, 17);
    } else {
        const int w = warp - 4, tid = threadIdx.x - 128;
        const uint32_t tag = ldg_rlx(&g_epoch) % 15u + 1u;
        bar_sync(NB_INIT, 288);
        bar_sync(NB_QPUB, 256);
#pragma unroll 1
        for (int b = 0; b < 2; b++) {
            const uint32_t* src = g_q + b * QW + kvh * 1024 + tid * 8;
            uint4 v0, v1;
            uint32_t spins = 0;
            while (true) {
                v0 = ldg_rlx4(src);
                v1 = ldg_rlx4(src + 4);
                if (__all_sync(~0u, ok4(v0, tag) && ok4(v1, tag))) break;
                if (++spins > SPIN_MAX) __trap();
                __nanosleep(100);
            }
            const uint32_t a = sm + SM_Q + (b * 8 + (tid >> 4)) * 272 + (tid & 15) * 16;
            sts64(a, pack_hi(v0.x, v0.y), pack_hi(v0.z, v0.w));
            sts64(a + 8, pack_hi(v1.x, v1.y), pack_hi(v1.z, v1.w));
            bar_arrive(b ? NB_Q1 : NB_Q0, 256);
        }
        if (!has_fin) return;
        const int ksp = c >> 2;
        uint32_t* const fin = fin_slot(c, 0, w, lane);
        if (PREW) { stg_rlx2(fin, 0, 0); stg_rlx2(fin + 1024, 0, 0); }
#pragma unroll 1
        for (int b = 0; b < 2; b++) {
            bar_sync(b ? NB_FLUSH1 : NB_FLUSH0, 256);
            if (b == 0) {
                if (tid < 56) {
                    const int hb = tid / 28, ch = tid % 28;
                    const uint32_t* src = g_h + hb * FF + ksp * 112 + ch * 4;
                    uint4 v;
                    uint32_t spins = 0;
                    while (true) {
                        v = ldg_rlx4(src);
                        if (ok4(v, tag)) break;
                        if (++spins > SPIN_MAX) __trap();
                        __nanosleep(200);
                    }
                    sts64(sm + SM_H + hb * 272 + ch * 8, pack_hi(v.x, v.y), pack_hi(v.z, v.w));
                }
                bar_arrive(NB_H, 256);
                __nanosleep(3000);
            }
            STAMP(tid == 0, 18 + 2 * b);
            const uint32_t* base = g_part + (b * 32 + ksp) * MEMBERS * REC;
            const int i4 = lane >> 3, j8 = lane & 7;
            const uint32_t* src = base + i4 * REC + w * 32 + j8 * 4;
            uint4 v[9];
            uint2 ml, ml32;
            v[8] = make_uint4(tag, tag, tag, tag);
            uint32_t pend = (i4 == 0 ? 0x1FF : 0xFF) | 0x600, spins = 0;
            while (true) {
                if (pend & 0x200) ml = ldg_rlx2(base + lane * REC + 128);
                if (pend & 0x400) ml32 = ldg_rlx2(base + 32 * REC + 128);
#pragma unroll
                for (int n = 0; n < 9; n++)
                    if (pend >> n & 1) v[n] = ldg_rlx4(src + n * 4 * REC);
                if ((((ml.x ^ tag) | (ml.y ^ tag)) & 0xF) == 0) pend &= ~0x200u;
                if ((((ml32.x ^ tag) | (ml32.y ^ tag)) & 0xF) == 0) pend &= ~0x400u;
#pragma unroll
                for (int n = 0; n < 9; n++)
                    if (ok4(v[n], tag)) pend &= ~(1u << n);
                if (__all_sync(~0u, pend == 0)) break;
                if (++spins > SPIN_MAX) __trap();
            }
            float M = fmaxf(untag(ml.x), untag(ml32.x));
#pragma unroll
            for (int s = 16; s; s >>= 1) M = fmaxf(M, __shfl_xor_sync(~0u, M, s));
            const float e = expd(untag(ml.x) - M), e32 = expd(untag(ml32.x) - M);
            float L = e * untag(ml.y);
#pragma unroll
            for (int s = 16; s; s >>= 1) L += __shfl_xor_sync(~0u, L, s);
            L = fmaf(e32, untag(ml32.y), L);
            float a0 = e32 * untag(v[8].x), a1 = e32 * untag(v[8].y), a2 = e32 * untag(v[8].z), a3 = e32 * untag(v[8].w);
#pragma unroll
            for (int n = 0; n < 8; n++) {
                const float en = __shfl_sync(~0u, e, i4 + 4 * n);
                a0 = fmaf(en, untag(v[n].x), a0);
                a1 = fmaf(en, untag(v[n].y), a1);
                a2 = fmaf(en, untag(v[n].z), a2);
                a3 = fmaf(en, untag(v[n].w), a3);
            }
#pragma unroll
            for (int s = 8; s < 32; s <<= 1) {
                a0 += __shfl_xor_sync(~0u, a0, s);
                a1 += __shfl_xor_sync(~0u, a1, s);
                a2 += __shfl_xor_sync(~0u, a2, s);
                a3 += __shfl_xor_sync(~0u, a3, s);
            }
            const float inv = 1.f / L;
            if (i4 == 0) sts64(sm + SM_O + b * 272 + (w * 32 + j8 * 4) * 2, pack_bf16(a0 * inv, a1 * inv), pack_bf16(a2 * inv, a3 * inv));
            STAMP(tid == 0, 19 + 2 * b);
        }
        bar_sync(NB_AUX, 128);
        tail_gemv<4, 2>(sm + SM_WO, sm + BAR_WO, sm + SM_O, fin, w, lane, tag);
        STAMP(tid == 0, 22);
    }
}

typedef CUresult (*EncodeFn)(CUtensorMap*, CUtensorMapDataType, cuuint32_t, void*, const cuuint64_t*, const cuuint64_t*,
                             const cuuint32_t*, const cuuint32_t*, CUtensorMapInterleave, CUtensorMapSwizzle,
                             CUtensorMapL2promotion, CUtensorMapFloatOOBfill);

void make_map(EncodeFn enc, CUtensorMap* m, const void* p, uint64_t d0, uint64_t d1, uint64_t d2, uint64_t s1, uint64_t s2,
              uint32_t b0, uint32_t b1, uint32_t b2, CUtensorMapSwizzle sw, CUtensorMapL2promotion pr) {
    cuuint64_t d[3] = {d0, d1, d2}, s[2] = {s1, s2};
    cuuint32_t b[3] = {b0, b1, b2}, e[3] = {1, 1, 1};
    enc(m, CU_TENSOR_MAP_DATA_TYPE_BFLOAT16, 3, const_cast<void*>(p), d, s, b, e, CU_TENSOR_MAP_INTERLEAVE_NONE, sw, pr,
        CU_TENSOR_MAP_FLOAT_OOB_FILL_NONE);
}

constexpr int h_t_wo = T_WO_DEF, h_t_wd = T_WD_DEF, h_t_thr = T_THR_DEF, h_depth = DEPTH_DEF;

}

extern "C" void kernel_launch(void* const* d_in, const int* in_sizes, int n_in, void* d_out, int out_size) {
    void* fn = nullptr;
    cudaDriverEntryPointQueryResult qr;
    cudaGetDriverEntryPoint("cuTensorMapEncodeTiled", &fn, cudaEnableDefault, &qr);
    EncodeFn enc = (EncodeFn)fn;
    Params P;
    const CUtensorMapL2promotion p128 = CU_TENSOR_MAP_L2_PROMOTION_L2_128B, p256 = CU_TENSOR_MAP_L2_PROMOTION_L2_256B;
    make_map(enc, &P.k, d_in[1], 64, 8 * SK, 2, 256, 128, 64, 64, 2, CU_TENSOR_MAP_SWIZZLE_128B, p256);
    make_map(enc, &P.v, d_in[2], 64, 8 * SK, 2, 256, 128, 64, 64, 2, CU_TENSOR_MAP_SWIZZLE_128B, p256);
    make_map(enc, &P.wq, d_in[3], QW, D_MODEL, 1, QW * 2, (uint64_t)QW * 2 * D_MODEL, 32, 256, 1, CU_TENSOR_MAP_SWIZZLE_64B, p128);
    make_map(enc, &P.wg, d_in[6], FF, D_MODEL, 1, FF * 2, (uint64_t)FF * 2 * D_MODEL, 32, 256, 1, CU_TENSOR_MAP_SWIZZLE_64B, p128);
    make_map(enc, &P.wu, d_in[7], FF, D_MODEL, 1, FF * 2, (uint64_t)FF * 2 * D_MODEL, 32, 256, 1, CU_TENSOR_MAP_SWIZZLE_64B, p128);
    make_map(enc, &P.wo, d_in[4], 64, QW, 16, 2048, 128, 64, 32, 4, CU_TENSOR_MAP_SWIZZLE_128B, p256);
    make_map(enc, &P.wd, d_in[8], 64, FF, 16, 2048, 128, 64, 16, 4, CU_TENSOR_MAP_SWIZZLE_128B, p256);
    P.x = (const __nv_bfloat16*)d_in[0];
    P.out = (__nv_bfloat16*)d_out;
    P.t_wo = h_t_wo;
    P.t_wd = h_t_wd;
    P.t_thr = h_t_thr;
    P.depth = h_depth;
    cudaFuncSetAttribute(fused_decode_kernel, cudaFuncAttributeMaxDynamicSharedMemorySize, SM_TOTAL);
    fused_decode_kernel<<<NCTA, 288, SM_TOTAL>>>(P);
}
```

```cpp
#include <cuda_runtime.h>
#include <cuda_bf16.h>
#include <cuda.h>
#include <stdint.h>

namespace {

constexpr int D_MODEL = 1024, SK = 32768, FF = 3584, QW = 4096;
constexpr int NCTA = 132;
constexpr int MEMBERS = 33;
constexpr int NTHREADS = 288;
constexpr int NSLOT = 6;
constexpr int SLOT = 16384;
constexpr int TILES_B = 512;
constexpr int TILES = 1024;
constexpr int GU_FIRST = 20;
constexpr int W_WO = 4, W_WD = 3;
constexpr int LAG_K = 16, LAG_V = 48;
constexpr int Q_DELAY = 2000;
constexpr int WO_PRE = 6;
constexpr int ACC_S = 80;
constexpr int HROWS = FF / 8;
constexpr int HSTR = (HROWS + 8) * 2;
constexpr int NOWN = 8, NSIL = 33;

constexpr int SM_WO = NSLOT * SLOT;
constexpr int SM_WD = SM_WO + 65536;
constexpr int SM_Q = SM_WD + 57344;
constexpr int SM_H = SM_Q + 2 * 8 * 136 * 2;
constexpr int SM_O = SM_H + 2 * HSTR;
constexpr int SM_RED = SM_O + 2 * 136 * 2;
constexpr int SM_ML = SM_RED + 3 * 4 * 64 * 4;
constexpr int SM_META = SM_ML + 4 * 8 * 2 * 4;
constexpr int SM_BAR = SM_META + 32;
constexpr int BAR_FULL = SM_BAR, BAR_EMPTY = BAR_FULL + 8 * NSLOT, BAR_WO = BAR_EMPTY + 8 * NSLOT,
              BAR_WD = BAR_WO + 8 * 8, BAR_GO = BAR_WD + 8 * 7, BAR_COMB = BAR_GO + 8 * 2,
              BAR_RED = BAR_COMB + 8;
constexpr int NBAR = 2 * NSLOT + 15 + 4;
constexpr int SM_TOTAL = SM_BAR + 8 * NBAR;
static_assert(SM_TOTAL <= 232448, "smem");

enum { NB_INIT = 0, NB_ATT = 1, NB_QPUB, NB_Q0, NB_Q1, NB_O, NB_AUX };

struct Params {
    const char *wq_raw, *wg_raw;
    CUtensorMap k, v, wq, wg, wu, wo, wd;
    const __nv_bfloat16* x;
    __nv_bfloat16* out;
    uint32_t* gs;
};

constexpr int G_CTR = 0;
constexpr int G_DONE = 32;
constexpr int G_Q = G_DONE + 4 * 32;
constexpr int G_H = G_Q + 2 * QW;
constexpr int G_ML = G_H + 2 * FF;
constexpr int G_PART = G_ML + 32 * 40 * 4;
constexpr int G_FIN = G_PART + 2 * 32 * MEMBERS * 128;
constexpr int G_ACC = G_FIN + 40 * 2 * D_MODEL;
constexpr int G_TOTAL = G_ACC + 2 * 128 * ACC_S;
__device__ __align__(1024) uint32_t g_s[G_TOTAL];

constexpr uint32_t SPIN_MAX = 1u << 20;

__device__ __forceinline__ bool elect_one() {
    uint32_t p;
    asm volatile("{\n.reg .pred p;\nelect.sync _|p, 0xffffffff;\nselp.u32 %0, 1, 0, p;\n}" : "=r"(p));
    return p;
}
__device__ __forceinline__ void mbar_init(uint32_t b, int c) {
    asm volatile("mbarrier.init.shared::cta.b64 [%0], %1;" ::"r"(b), "r"(c) : "memory");
}
__device__ __forceinline__ void mbar_expect(uint32_t b, uint32_t bytes) {
    asm volatile("mbarrier.arrive.expect_tx.shared::cta.b64 _, [%0], %1;" ::"r"(b), "r"(bytes) : "memory");
}
__device__ __forceinline__ void mbar_arrive(uint32_t b) {
    asm volatile("mbarrier.arrive.shared::cta.b64 _, [%0];" ::"r"(b) : "memory");
}
__device__ __forceinline__ bool mbar_try(uint32_t b, uint32_t ph) {
    uint32_t ok;
    asm volatile("{\n.reg .pred p;\nmbarrier.try_wait.parity.shared::cta.b64 p, [%1], %2;\nselp.u32 %0, 1, 0, p;\n}"
                 : "=r"(ok) : "r"(b), "r"(ph) : "memory");
    return ok;
}
__device__ __forceinline__ void mbar_wait(uint32_t b, uint32_t ph) {
    if (__builtin_expect(!mbar_try(b, ph), 0))
        asm volatile(
            "{\n.reg .pred p;\n.reg .u32 n;\nmov.u32 n, 0;\n"
            "WAIT:\nmbarrier.try_wait.parity.shared::cta.b64 p, [%0], %1;\n@p bra DONE;\n"
            "add.u32 n, n, 1;\nsetp.lt.u32 p, n, 0x100000;\n@p bra WAIT;\ntrap;\nDONE:\n}" ::"r"(b), "r"(ph) : "memory");
}
__device__ __forceinline__ bool mbar_test(uint32_t b, uint32_t ph) {
    uint32_t ok;
    asm volatile("{\n.reg .pred p;\nmbarrier.test_wait.parity.shared::cta.b64 p, [%1], %2;\nselp.u32 %0, 1, 0, p;\n}"
                 : "=r"(ok) : "r"(b), "r"(ph) : "memory");
    return ok;
}
__device__ __forceinline__ void tma3(uint32_t dst, const CUtensorMap* m, int c0, int c1, int c2, uint32_t bar,
                                     uint64_t pol) {
    asm volatile(
        "cp.async.bulk.tensor.3d.shared::cluster.global.mbarrier::complete_tx::bytes.L2::cache_hint "
        "[%0], [%1, {%3,%4,%5}], [%2], %6;" ::"r"(dst), "l"(m), "r"(bar), "r"(c0), "r"(c1), "r"(c2), "l"(pol)
        : "memory");
}
__device__ __forceinline__ void bar_sync(int id, int n) { asm volatile("bar.sync %0, %1;" ::"r"(id), "r"(n) : "memory"); }
__device__ __forceinline__ void bar_arrive(int id, int n) { asm volatile("bar.arrive %0, %1;" ::"r"(id), "r"(n) : "memory"); }

__device__ __forceinline__ void ldsm4(uint32_t a, uint32_t (&r)[4]) {
    asm volatile("ldmatrix.sync.aligned.m8n8.x4.shared.b16 {%0,%1,%2,%3}, [%4];"
                 : "=r"(r[0]), "=r"(r[1]), "=r"(r[2]), "=r"(r[3]) : "r"(a) : "memory");
}
__device__ __forceinline__ void ldsm4t(uint32_t a, uint32_t (&r)[4]) {
    asm volatile("ldmatrix.sync.aligned.m8n8.x4.trans.shared.b16 {%0,%1,%2,%3}, [%4];"
                 : "=r"(r[0]), "=r"(r[1]), "=r"(r[2]), "=r"(r[3]) : "r"(a) : "memory");
}
__device__ __forceinline__ void mma(float (&c)[4], const uint32_t (&a)[4], uint32_t b0, uint32_t b1) {
    asm volatile("mma.sync.aligned.m16n8k16.row.col.f32.bf16.bf16.f32 {%0,%1,%2,%3}, {%4,%5,%6,%7}, {%8,%9}, {%0,%1,%2,%3};"
                 : "+f"(c[0]), "+f"(c[1]), "+f"(c[2]), "+f"(c[3])
                 : "r"(a[0]), "r"(a[1]), "r"(a[2]), "r"(a[3]), "r"(b0), "r"(b1));
}
__device__ __forceinline__ uint32_t movm(uint32_t a) {
    uint32_t d;
    asm volatile("movmatrix.sync.aligned.m8n8.trans.b16 %0, %1;" : "=r"(d) : "r"(a));
    return d;
}
__device__ __forceinline__ uint32_t pack_bf16(float lo, float hi) {
    uint32_t d;
    asm("cvt.rn.bf16x2.f32 %0, %1, %2;" : "=r"(d) : "f"(hi), "f"(lo));
    return d;
}
__device__ __forceinline__ float bf_lo(uint32_t v) { return __uint_as_float(v << 16); }
__device__ __forceinline__ float bf_hi(uint32_t v) { return __uint_as_float(v & 0xffff0000u); }
__device__ __forceinline__ float rbf(float x) { return __bfloat162float(__float2bfloat16_rn(x)); }
__device__ __forceinline__ float expd(float x) {
    float y;
    asm("ex2.approx.ftz.f32 %0, %1;" : "=f"(y) : "f"(x * 1.4426950408889634f));
    return y;
}
__device__ __forceinline__ uint32_t lds32(uint32_t a) {
    uint32_t v;
    asm volatile("ld.shared.u32 %0, [%1];" : "=r"(v) : "r"(a) : "memory");
    return v;
}
__device__ __forceinline__ float4 lds128f(uint32_t a) {
    float4 v;
    asm volatile("ld.shared.v4.f32 {%0,%1,%2,%3}, [%4];" : "=f"(v.x), "=f"(v.y), "=f"(v.z), "=f"(v.w) : "r"(a) : "memory");
    return v;
}
__device__ __forceinline__ void sts32(uint32_t a, uint32_t v) { asm volatile("st.shared.u32 [%0], %1;" ::"r"(a), "r"(v) : "memory"); }
__device__ __forceinline__ void sts32f(uint32_t a, float v) { asm volatile("st.shared.f32 [%0], %1;" ::"r"(a), "f"(v) : "memory"); }
__device__ __forceinline__ void sts64(uint32_t a, uint32_t x, uint32_t y) {
    asm volatile("st.shared.v2.u32 [%0], {%1,%2};" ::"r"(a), "r"(x), "r"(y) : "memory");
}
constexpr uint64_t NORMAL = 0x1000000000000000ull;
__device__ __forceinline__ uint32_t ldg_rlx(const uint32_t* p) {
    uint32_t v;
    asm volatile("ld.relaxed.gpu.global.L2::cache_hint.u32 %0, [%1], %2;" : "=r"(v) : "l"(p), "l"(NORMAL) : "memory");
    return v;
}
__device__ __forceinline__ uint2 ldg_rlx2(const uint32_t* p) {
    uint2 v;
    asm volatile("ld.relaxed.gpu.global.L2::cache_hint.v2.u32 {%0,%1}, [%2], %3;" : "=r"(v.x), "=r"(v.y) : "l"(p), "l"(NORMAL) : "memory");
    return v;
}
__device__ __forceinline__ uint4 ldg_rlx4(const uint32_t* p) {
    uint4 v;
    asm volatile("ld.relaxed.gpu.global.L2::cache_hint.v4.u32 {%0,%1,%2,%3}, [%4], %5;"
                 : "=r"(v.x), "=r"(v.y), "=r"(v.z), "=r"(v.w) : "l"(p), "l"(NORMAL) : "memory");
    return v;
}
__device__ __forceinline__ void stg_rlx(uint32_t* p, uint32_t v) {
    asm volatile("st.relaxed.gpu.global.L2::cache_hint.u32 [%0], %1, %2;" ::"l"(p), "r"(v), "l"(NORMAL) : "memory");
}
__device__ __forceinline__ void stg_rlx2(uint32_t* p, uint32_t x, uint32_t y) {
    asm volatile("st.relaxed.gpu.global.L2::cache_hint.v2.u32 [%0], {%1,%2}, %3;" ::"l"(p), "r"(x), "r"(y), "l"(NORMAL) : "memory");
}
__device__ __forceinline__ void stg_rlx4(uint32_t* p, uint32_t x, uint32_t y, uint32_t z, uint32_t w) {
    asm volatile("st.relaxed.gpu.global.L2::cache_hint.v4.u32 [%0], {%1,%2,%3,%4}, %5;" ::"l"(p), "r"(x), "r"(y), "r"(z), "r"(w),
                 "l"(NORMAL) : "memory");
}
__device__ __forceinline__ void signal_done(uint32_t* ctr) {
    asm volatile("red.relaxed.gpu.global.inc.L2::cache_hint.u32 [%0], %1, %2;" ::"l"(ctr), "n"(15 * MEMBERS - 1), "l"(NORMAL) : "memory");
}
__device__ __forceinline__ uint32_t launch_tag(const uint32_t* done) { return ldg_rlx(done) / MEMBERS + 1; }
__device__ __forceinline__ uint32_t tagf(float v, uint32_t tag) { return (__float_as_uint(v) & ~0xFu) | tag; }
__device__ __forceinline__ float untag(uint32_t w) { return __uint_as_float(w & ~0xFu); }
__device__ __forceinline__ bool ok4(const uint4& v, uint32_t tag) {
    return ((((v.x ^ tag) | (v.y ^ tag)) | ((v.z ^ tag) | (v.w ^ tag))) & 0xFu) == 0;
}
__device__ __forceinline__ void or_xor(uint32_t& acc, uint32_t w, uint32_t tag) {
    asm("lop3.b32 %0, %0, %1, %2, 0xF6;" : "+r"(acc) : "r"(w), "r"(tag));
}
__device__ __forceinline__ uint32_t pack_hi(uint32_t a, uint32_t b) { return __byte_perm(a, b, 0x7632); }

constexpr float FIX = 17592186044416.f;
__device__ __forceinline__ unsigned long long* acc_ptr(uint32_t* gs, int e) {
    return reinterpret_cast<unsigned long long*>(gs + G_ACC) + (e >> 4) * ACC_S + (e & 15);
}
__device__ __forceinline__ bool fits(float v) { return fabsf(v) < 8192.f; }
__device__ __forceinline__ bool tiny(float sum, float own) { return fabsf(sum) < 1.f / 32768.f && fabsf(own) < 0.125f; }
__device__ __forceinline__ unsigned long long to_fixed(float v) { return (unsigned long long)__float2ll_rn(v * FIX) & ~0xFFFull; }
__device__ __forceinline__ void red_add(unsigned long long* p, unsigned long long v) {
    asm volatile("red.relaxed.gpu.global.add.L2::cache_hint.u64 [%0], %1, %2;" ::"l"(p), "l"(v), "l"(NORMAL) : "memory");
}
__device__ __forceinline__ unsigned long long atom_add(unsigned long long* p, unsigned long long v) {
    unsigned long long o;
    asm volatile("atom.relaxed.gpu.global.add.L2::cache_hint.u64 %0, [%1], %2, %3;" : "=l"(o) : "l"(p), "l"(v), "l"(NORMAL) : "memory");
    return o;
}
__device__ __forceinline__ void flag_range(unsigned long long* p) {
    asm volatile("red.relaxed.gpu.global.or.b64 [%0], 0x800;" ::"l"(p) : "memory");
}
__device__ __forceinline__ void add_silent(float v, unsigned long long* acc) {
    if (!fits(v)) flag_range(acc);
    red_add(acc, (fits(v) ? to_fixed(v) : 0) | 32);
}
__device__ __noinline__ float finish_slow(uint32_t* gs, unsigned long long tot, int e, float own, float x, uint32_t tag) {
    uint32_t spins = 0;
    while (((tot >> 5) & 0x3F) != NSIL) {
        asm volatile("ld.relaxed.gpu.global.u64 %0, [%1];" : "=l"(tot) : "l"(acc_ptr(gs, e)) : "memory");
        if (++spins > SPIN_MAX) __trap();
    }
    float sum = __ll2float_rn((long long)tot) * (1.f / FIX);
    if ((tot & 0x800) || tiny(sum, own)) {
        uint32_t wv[40];
        bool ok;
        do {
            ok = true;
#pragma unroll
            for (int u = 0; u < 40; u++) wv[u] = ldg_rlx(gs + G_FIN + u * 2 * D_MODEL + e);
#pragma unroll
            for (int u = 0; u < 40; u++) ok &= (wv[u] & 0xF) == tag;
            if (++spins > SPIN_MAX) __trap();
        } while (!ok);
        sum = x;
#pragma unroll
        for (int u = 0; u < 40; u++) sum += untag(wv[u]);
    }
    return sum;
}

__device__ __forceinline__ float pick(const float (&a)[4], int lane) {
    return (lane & 2) ? ((lane & 1) ? a[3] : a[2]) : ((lane & 1) ? a[1] : a[0]);
}
__device__ __forceinline__ int lane_elem(int lane) { return ((lane >> 2) + 8 * ((lane >> 1) & 1)) * 2 + (lane & 1); }

__global__ void __launch_bounds__(NTHREADS, 1) fused_decode_kernel(const __grid_constant__ Params P) {
    extern __shared__ __align__(1024) unsigned char smem_raw[];
    const uint32_t sm = (uint32_t)__cvta_generic_to_shared(smem_raw);
    constexpr uint64_t pol = 0x12F0000000000000ull;
    if (threadIdx.x >= 32) {
        const int c = blockIdx.x, id = threadIdx.x - 32, row = id >> 2;
        const uint32_t stride = c < 128 ? QW * 2 : FF * 2;
        const char* src = (c < 128 ? P.wq_raw : P.wg_raw) + c * 64 + (id & 3) * 16 + row * stride;
        const uint32_t dst = sm + row * 64 + (((id & 3) ^ ((row >> 1) & 3)) << 4);
#pragma unroll
        for (int i = 0; i < 4; i++)
            asm volatile("cp.async.cg.shared.global.L2::cache_hint.L2::128B [%0], [%1], 16, %2;" ::"r"(dst + i * 4096),
                         "l"(src + i * 64 * stride), "l"(pol) : "memory");
    }
    if (threadIdx.x < 32 && elect_one()) {
        const int c = blockIdx.x;
        const bool has_q = c < 128;
        const int c0 = has_q ? c * 32 : (c - GU_FIRST) * 32;
        mbar_init(sm + BAR_FULL + 8, 1);
        asm volatile("fence.mbarrier_init.release.cluster;" ::: "memory");
        tma3(sm + SLOT, has_q ? &P.wq : &P.wu, c0, has_q ? 256 : 0, 0, sm + BAR_FULL + 8, pol);
        if (mbar_test(sm + BAR_FULL + 8, 1)) {
            mbar_expect(sm + BAR_FULL + 8, SLOT);
            mbar_init(sm + BAR_FULL + 16, 1);
            mbar_init(sm + BAR_FULL + 24, 1);
            asm volatile("fence.mbarrier_init.release.cluster;" ::: "memory");
#pragma unroll
            for (int i = 2; i < 4; i++) {
                mbar_expect(sm + BAR_FULL + i * 8, SLOT);
                tma3(sm + i * SLOT, has_q ? &P.wq : (i & 1) ? &P.wu : &P.wg, c0, (has_q ? i : 1) * 256, 0, sm + BAR_FULL + i * 8, pol);
            }
            mbar_init(sm + BAR_FULL, 1);
            mbar_arrive(sm + BAR_FULL);
#pragma unroll
            for (int i = 4; i < NBAR; i++) mbar_init(sm + SM_BAR + i * 8, ((i >= NSLOT && i < 2 * NSLOT) || i == NBAR - 1) ? 4 : 1);
            asm volatile("fence.mbarrier_init.release.cluster;" ::: "memory");
            sts32(sm + SM_META + 7 * 4, 0);
        }
    }
    int c, tx;
    asm volatile("mov.u32 %0, %%ctaid.x;" : "=r"(c));
    asm volatile("mov.u32 %0, %%tid.x;" : "=r"(tx));
    const int warp = tx >> 5, lane = tx & 31;
    const int kvh = c & 3, member = c >> 2;
    const int cb = member & 3, ksp = kvh * 8 + (member >> 2);
    const int cbd = c & 15, ksd = c >> 4;
    const bool has_q = c < 128, has_gu = c >= GU_FIRST, has_fin = c < 128;

    if (warp == 0) {
        __syncwarp();
        bar_arrive(NB_INIT, NTHREADS);
        if (elect_one()) {
            unsigned long long* const ctr = reinterpret_cast<unsigned long long*>(P.gs + G_CTR);
            constexpr unsigned long long ALL = 0x0001000100010001ull;
            unsigned long long cl = (member - MEMBERS) * ALL;
            asm volatile("prefetch.tensormap [%0];" ::"l"(&P.wg) : "memory");
            asm volatile("prefetch.tensormap [%0];" ::"l"(&P.wu) : "memory");
            asm volatile("prefetch.tensormap [%0];" ::"l"(&P.k) : "memory");
            asm volatile("prefetch.tensormap [%0];" ::"l"(&P.v) : "memory");
            asm volatile("prefetch.tensormap [%0];" ::"l"(&P.wo) : "memory");
            asm volatile("prefetch.tensormap [%0];" ::"l"(&P.wd) : "memory");
            uint32_t win[4];
#pragma unroll
            for (int i = 0; i < 4; i++) win[i] = sm + BAR_FULL + i * 8;
            int slot = 4;
            uint32_t sph = 0;
            auto advance = [&]() { if (++slot == NSLOT) { slot = 0; sph ^= 1; } };
            auto ring_load = [&](const CUtensorMap* m, int c0, int c1, bool wide) {
                const uint32_t fb = sm + BAR_FULL + slot * 8;
                mbar_wait(sm + BAR_EMPTY + slot * 8, sph ^ 1);
                sts32(sm + SM_META + slot * 4, 0);
                mbar_expect(fb, SLOT);
                const uint32_t e = wide ? win[0] : win[1];
                mbar_wait(e & ~1u, e & 1u);
                tma3(sm + slot * SLOT, m, c0, c1, 0, fb, pol);
                win[0] = win[1]; win[1] = win[2]; win[2] = win[3]; win[3] = fb | sph;
                advance();
            };
            auto flush_mark = [&]() {
                mbar_wait(sm + BAR_EMPTY + slot * 8, sph ^ 1);
                sts32(sm + SM_META + slot * 4, 1);
                mbar_arrive(sm + BAR_FULL + slot * 8);
                advance();
            };
            if (has_fin) {
#pragma unroll
                for (int i = 0; i < 15; i++) mbar_expect(sm + BAR_WO + i * 8, 8192);
            }
            if (has_gu) {
#pragma unroll 1
                for (int u = has_q ? 0 : 4; u < 8; u++) ring_load((u & 1) ? &P.wu : &P.wg, (c - GU_FIRST) * 32, (u >> 1) * 256, false);
            }
            bool b1 = false, go0 = false;
            const uint32_t t_go0 = TILES_B + 96 + 3 * member;
            uint32_t t;
#pragma unroll 1
            while ((t = (uint32_t)((cl += MEMBERS * ALL) >> (16 * kvh)) & 0xFFFF) < TILES) {
                const int lag = (int)(((uint32_t)cl & 0xFFFF) + ((uint32_t)cl >> 16) + ((uint32_t)(cl >> 32) & 0xFFFF) +
                                      (uint32_t)(cl >> 48)) - 4 * (int)t;
                cl = atom_add(ctr, 1ull << (16 * kvh));
                if (t >= TILES_B && !b1) { flush_mark(); b1 = true; }
                if (t >= t_go0 && !go0) { mbar_arrive(sm + BAR_GO); go0 = true; }
                const int row = ((t >> 9) * 4 + kvh) * SK + (t & (TILES_B - 1)) * 64;
                ring_load(&P.k, 0, row, lag > LAG_K);
                ring_load(&P.v, 0, row, lag > LAG_V);
            }
            if (!b1) flush_mark();
            flush_mark();
            if (!go0) mbar_arrive(sm + BAR_GO);
            if (has_fin) {
                bool open = false;
#pragma unroll 1
                for (int i = 0; i < 15; i++) {
                    uint32_t e = sm + BAR_WO + (i - (i < 8 ? W_WO : W_WD)) * 8;
#pragma unroll
                    for (int k = 0; k < 4; k++) e = (i < W_WO && ((W_WO - 1 - i) >> 1) == 3 - k) ? win[k] : e;
                    if (i == 8) open = false;
                    uint32_t spins = 0;
                    while (!open) {
                        const bool landed = mbar_test(e & ~1u, e & 1u);
                        open = mbar_test(sm + (i < 8 ? BAR_COMB : BAR_RED), 0);
                        if (landed) break;
                        if (++spins > (SPIN_MAX << 4)) __trap();
                    }
                    tma3(sm + SM_WO + i * 8192, i < 8 ? &P.wo : &P.wd, 0, i < 8 ? ksp * 128 + i * 16 : ksd * HROWS + (i - 8) * 64,
                         i < 8 ? cb * 4 : cbd, sm + BAR_WO + i * 8, pol);
                }
            }
        }
    } else if (warp < 5) {
        const int w = warp - 1, tid = tx - 32;
        const int g = lane >> 2, t = lane & 3;
        const int j = lane >> 3, r = lane & 7;
        const uint32_t tag = launch_tag(P.gs + G_DONE + kvh * 32);
        uint32_t xf[4][2];
        {
            const uint4* xv = reinterpret_cast<const uint4*>(P.x);
            uint4 u[2][4];
#pragma unroll
            for (int b = 0; b < 2; b++)
#pragma unroll
                for (int i = 0; i < 4; i++) u[b][i] = __ldg(xv + b * 128 + i * 32 + lane);
            const uint32_t* xe = reinterpret_cast<const uint32_t*>(P.x + (g & 1) * D_MODEL + (g >> 1) * 256 + w * 64 + 2 * t);
#pragma unroll
            for (int ks = 0; ks < 4; ks++) { xf[ks][0] = __ldg(xe + ks * 8); xf[ks][1] = __ldg(xe + ks * 8 + 4); }
            float mean[2], var[2];
#pragma unroll
            for (int b = 0; b < 2; b++) {
                float s = 0.f;
#pragma unroll
                for (int i = 0; i < 4; i++)
                    s += ((bf_lo(u[b][i].x) + bf_hi(u[b][i].x)) + (bf_lo(u[b][i].y) + bf_hi(u[b][i].y))) +
                         ((bf_lo(u[b][i].z) + bf_hi(u[b][i].z)) + (bf_lo(u[b][i].w) + bf_hi(u[b][i].w)));
#pragma unroll
                for (int o = 16; o; o >>= 1) s += __shfl_xor_sync(~0u, s, o);
                mean[b] = s * (1.f / D_MODEL);
                float q = 0.f;
#pragma unroll
                for (int i = 0; i < 4; i++) {
                    const uint32_t e[4] = {u[b][i].x, u[b][i].y, u[b][i].z, u[b][i].w};
#pragma unroll
                    for (int k = 0; k < 4; k++) {
                        const float d0 = bf_lo(e[k]) - mean[b], d1 = bf_hi(e[k]) - mean[b];
                        q = fmaf(d0, d0, q);
                        q = fmaf(d1, d1, q);
                    }
                }
#pragma unroll
                for (int o = 16; o; o >>= 1) q += __shfl_xor_sync(~0u, q, o);
                var[b] = q * (1.f / D_MODEL);
            }
            const float mu = rbf((g & 1) ? mean[1] : mean[0]);
            const float rs = 1.f / rbf(sqrtf(rbf(rbf((g & 1) ? var[1] : var[0]) + 1e-5f)));
#pragma unroll
            for (int ks = 0; ks < 4; ks++)
#pragma unroll
                for (int h = 0; h < 2; h++)
                    xf[ks][h] = pack_bf16(rbf(bf_lo(xf[ks][h]) - mu) * rs, rbf(bf_hi(xf[ks][h]) - mu) * rs);
        }
        asm volatile("cp.async.wait_all;\nfence.proxy.async.shared::cta;" ::: "memory");
        bar_sync(NB_INIT, NTHREADS);
        int slot = 0;
        uint32_t sph = 0;
        auto advance = [&]() { if (++slot == NSLOT) { slot = 0; sph ^= 1; } };
        auto release = [&]() {
            __syncwarp();
            if (lane == 0) mbar_arrive(sm + BAR_EMPTY + slot * 8);
            advance();
        };
        const uint32_t p1off = (w * 64 + (j >> 1) * 8 + r) * 64;
        auto p1_box = [&](float (&acc)[2][4], int rb) {
            mbar_wait(sm + BAR_FULL + slot * 8, sph);
            const bool live = (g >> 1) == rb;
#pragma unroll
            for (int ks = 0; ks < 4; ks++) {
                const uint32_t b0 = live ? xf[ks][0] : 0u, b1 = live ? xf[ks][1] : 0u;
#pragma unroll
                for (int mt = 0; mt < 2; mt++) {
                    uint32_t a[4];
                    ldsm4t(sm + slot * SLOT + p1off + ks * 1024 + (((2 * mt + (j & 1)) ^ (r >> 1)) << 4), a);
                    mma(acc[mt], a, b0, b1);
                }
            }
            release();
        };
        auto p1_store = [&](float (&acc)[2][4], int unit) {
#pragma unroll
            for (int mt = 0; mt < 2; mt++)
#pragma unroll
                for (int e = 0; e < 4; e++) {
                    float v = acc[mt][e];
                    v += __shfl_xor_sync(~0u, v, 1);
                    v += __shfl_xor_sync(~0u, v, 2);
                    if (t == 0) sts32f(sm + SM_RED + ((unit * 4 + w) * 64 + (e & 1) * 32 + mt * 16 + (e >> 1) * 8 + g) * 4, v);
                }
        };
        auto p1_sum = [&](int unit, int i) {
            const uint32_t a = sm + SM_RED + (unit * 256 + i) * 4;
            return (__uint_as_float(lds32(a)) + __uint_as_float(lds32(a + 256))) +
                   (__uint_as_float(lds32(a + 512)) + __uint_as_float(lds32(a + 768)));
        };
        if (has_q) {
            float acc[2][4] = {};
#pragma unroll 1
            for (int rb = 0; rb < 4; rb++) p1_box(acc, rb);
            p1_store(acc, 0);
            bar_sync(NB_ATT, 128);
            if (w < 2) stg_rlx(P.gs + G_Q + w * QW + c * 32 + lane, __float_as_uint(rbf(p1_sum(0, w * 32 + lane))) | tag);
            bar_arrive(NB_QPUB, 256);
        }
        if (has_gu) {
            float ag[2][4] = {}, au[2][4] = {};
#pragma unroll 1
            for (int rb = 0; rb < 4; rb++) {
                p1_box(ag, rb);
                p1_box(au, rb);
                if (!has_q && rb == 1) bar_arrive(NB_QPUB, 256);
            }
            p1_store(ag, 1);
            p1_store(au, 2);
            bar_sync(NB_ATT, 128);
            if (w < 2) {
                const float gt = rbf(p1_sum(1, w * 32 + lane)), up = rbf(p1_sum(2, w * 32 + lane));
                const float in = 0.7978845608028654f * (gt + 0.044715f * gt * gt * gt);
                const float ge = rbf(0.5f * gt * (1.f + tanhf(in)));
                stg_rlx(P.gs + G_H + w * FF + (c - GU_FIRST) * 32 + lane, __float_as_uint(rbf(ge * up)) | tag);
            }
        }
        const int elem = (cbd * 4 + w) * 32 + lane_elem(lane), oidx = (elem & 1) * D_MODEL + (elem >> 1);
        unsigned long long* const acc = acc_ptr(P.gs, elem);
        const float xres = __bfloat162float(P.x[oidx]);
        const uint32_t koff = (w * 16 + (j & 1) * 8 + r) * 128;
        const uint32_t voff = (w * 16 + (j >> 1) * 8 + r) * 128;
#pragma unroll 1
        for (int b = 0; b < 2; b++) {
            bar_sync(b ? NB_Q1 : NB_Q0, 256);
            uint32_t qf[8][2];
#pragma unroll
            for (int ks = 0; ks < 8; ks++) {
                const uint32_t a = sm + SM_Q + (b * 8 + g) * 272 + ks * 32 + t * 4;
                qf[ks][0] = lds32(a);
                qf[ks][1] = lds32(a + 16);
            }
            float o[8][4];
#pragma unroll
            for (int i = 0; i < 8; i++) o[i][0] = o[i][1] = o[i][2] = o[i][3] = 0.f;
            float m0 = __uint_as_float(0xFF7F0000u), m1 = m0, l0 = 0.f, l1 = 0.f;
#pragma unroll 1
            while (true) {
                mbar_wait(sm + BAR_FULL + slot * 8, sph);
                if (lds32(sm + SM_META + slot * 4)) break;
                float sa[4] = {0.f, 0.f, 0.f, 0.f}, sb[4] = {0.f, 0.f, 0.f, 0.f};
                const uint32_t kb = sm + slot * SLOT + koff;
#pragma unroll
                for (int ks = 0; ks < 4; ks++) {
                    uint32_t a0[4], a1[4];
                    const uint32_t sw = ((2 * ks + (j >> 1)) ^ r) << 4;
                    ldsm4(kb + sw, a0);
                    ldsm4(kb + 8192 + sw, a1);
                    mma(sa, a0, qf[ks][0], qf[ks][1]);
                    mma(sb, a1, qf[ks + 4][0], qf[ks + 4][1]);
                }
                release();
                float s[4];
                {
                    const uint32_t p01 = pack_bf16(sa[0] + sb[0], sa[1] + sb[1]), p23 = pack_bf16(sa[2] + sb[2], sa[3] + sb[3]);
                    const float sc = 0.08838834764831845f;
                    const uint32_t q01 = pack_bf16(bf_lo(p01) * sc, bf_hi(p01) * sc), q23 = pack_bf16(bf_lo(p23) * sc, bf_hi(p23) * sc);
                    s[0] = bf_lo(q01); s[1] = bf_hi(q01); s[2] = bf_lo(q23); s[3] = bf_hi(q23);
                }
                float x0 = fmaxf(s[0], s[2]), x1 = fmaxf(s[1], s[3]);
                if (__any_sync(~0u, x0 > m0 || x1 > m1)) {
#pragma unroll
                    for (int sft = 4; sft < 32; sft <<= 1) {
                        x0 = fmaxf(x0, __shfl_xor_sync(~0u, x0, sft));
                        x1 = fmaxf(x1, __shfl_xor_sync(~0u, x1, sft));
                    }
                    x0 = fmaxf(x0, m0);
                    x1 = fmaxf(x1, m1);
                    const float r0 = expd(m0 - x0), r1 = expd(m1 - x1);
                    m0 = x0; m1 = x1;
                    l0 *= r0; l1 *= r1;
#pragma unroll
                    for (int i = 0; i < 8; i++) { o[i][0] *= r0; o[i][1] *= r1; o[i][2] *= r0; o[i][3] *= r1; }
                }
                const float p0 = expd(s[0] - m0), p1 = expd(s[1] - m1), p2 = expd(s[2] - m0), p3 = expd(s[3] - m1);
                l0 += p0 + p2;
                l1 += p1 + p3;
                const uint32_t pb0 = movm(pack_bf16(p0, p1)), pb1 = movm(pack_bf16(p2, p3));
                mbar_wait(sm + BAR_FULL + slot * 8, sph);
                const uint32_t vb = sm + slot * SLOT + voff;
#pragma unroll
                for (int mt = 0; mt < 4; mt++) {
                    uint32_t a0[4], a1[4];
                    const uint32_t sw = ((2 * mt + (j & 1)) ^ r) << 4;
                    ldsm4t(vb + sw, a0);
                    ldsm4t(vb + 8192 + sw, a1);
                    mma(o[mt], a0, pb0, pb1);
                    mma(o[mt + 4], a1, pb0, pb1);
                }
                release();
            }
            const uint32_t mb = sm + slot * SLOT;
#pragma unroll
            for (int mt = 0; mt < 8; mt++) {
#pragma unroll
                for (int e = 0; e < 4; e++) {
                    const int d = mt * 16 + (e >> 1) * 8 + g, hd = 2 * t + (e & 1);
                    sts32f(mb + w * 4096 + hd * 512 + ((d * 4) ^ (t << 5)), o[mt][e]);
                }
                if (mt < 6 && !(mt & 1)) {
                    l0 += __shfl_xor_sync(~0u, l0, 4 << (mt >> 1));
                    l1 += __shfl_xor_sync(~0u, l1, 4 << (mt >> 1));
                }
            }
            if (g == 0) {
                sts64(sm + SM_ML + (w * 8 + 2 * t) * 8, __float_as_uint(m0), __float_as_uint(l0));
                sts64(sm + SM_ML + (w * 8 + 2 * t + 1) * 8, __float_as_uint(m1), __float_as_uint(l1));
            }
            bar_sync(NB_ATT, 128);
            {
                const int hd = tid >> 4, ch = tid & 15;
                float mw[4], lw[4];
#pragma unroll
                for (int i = 0; i < 4; i++) {
                    mw[i] = __uint_as_float(lds32(sm + SM_ML + (i * 8 + hd) * 8));
                    lw[i] = __uint_as_float(lds32(sm + SM_ML + (i * 8 + hd) * 8 + 4));
                }
                const float M = fmaxf(fmaxf(mw[0], mw[1]), fmaxf(mw[2], mw[3]));
                float L = 0.f;
                float4 s0 = {0.f, 0.f, 0.f, 0.f}, s1 = s0;
#pragma unroll
                for (int i = 0; i < 4; i++) {
                    const float e = expd(mw[i] - M);
                    L = fmaf(e, lw[i], L);
                    const uint32_t a = mb + i * 4096 + hd * 512;
                    const float4 u0 = lds128f(a + ((ch * 16) ^ ((hd >> 1) << 5)));
                    const float4 u1 = lds128f(a + ((ch * 16 + 256) ^ ((hd >> 1) << 5)));
                    s0.x = fmaf(e, u0.x, s0.x); s0.y = fmaf(e, u0.y, s0.y); s0.z = fmaf(e, u0.z, s0.z); s0.w = fmaf(e, u0.w, s0.w);
                    s1.x = fmaf(e, u1.x, s1.x); s1.y = fmaf(e, u1.y, s1.y); s1.z = fmaf(e, u1.z, s1.z); s1.w = fmaf(e, u1.w, s1.w);
                }
                uint32_t* rec = P.gs + G_PART + ((b * 32 + kvh * 8 + hd) * MEMBERS + member) * 128;
                stg_rlx4(rec + ch * 4, tagf(s0.x, tag), tagf(s0.y, tag), tagf(s0.z, tag), tagf(s0.w, tag));
                stg_rlx4(rec + 64 + ch * 4, tagf(s1.x, tag), tagf(s1.y, tag), tagf(s1.z, tag), tagf(s1.w, tag));
                uint32_t* ml = P.gs + G_ML + ((kvh * 8 + hd) * 40 + member) * 4;
                if (ch == 0) stg_rlx2(ml + 2 * b, tagf(M, tag), tagf(L, tag));
            }
            if (b == 1 && tid == 0) {
                signal_done(P.gs + G_DONE + kvh * 32);
                mbar_arrive(sm + BAR_GO + 8);
            }
            if (b == 0 && ksd == 0) add_silent(xres, acc);
            asm volatile("fence.proxy.async.shared::cta;" ::: "memory");
            release();
        }
        if (!has_fin) return;
        {
            const int e0 = (cb * 4 + w) * 128 + lane_elem(lane);
            unsigned long long* oacc = acc_ptr(P.gs, e0);
            asm volatile("" : "+l"(oacc));
            const uint32_t ra = sm + SM_WO + w * 2048 + ((j >> 1) * 8 + r) * 128;
            uint32_t wf[8][4][4];
            auto fetch = [&](int bx) {
#pragma unroll
                for (int mt = 0; mt < 4; mt++) ldsm4t(ra + bx * 8192 + (((2 * mt + (j & 1)) ^ r) << 4), wf[bx][mt]);
            };
#pragma unroll
            for (int bx = 0; bx < 8; bx++) {
                mbar_wait(sm + BAR_WO + bx * 8, 0);
                if (bx < WO_PRE) fetch(bx);
            }
            bar_sync(NB_O, 256);
            float oa[8][4] = {};
            const uint32_t vb = sm + SM_O + (g & 1) * 272 + t * 4;
#pragma unroll
            for (int bx = 0; bx < 8; bx++) {
                const uint32_t b0 = lds32(vb + bx * 32), b1 = lds32(vb + bx * 32 + 16);
#pragma unroll
                for (int mt = 0; mt < 4; mt++) mma(oa[(bx & 1) * 4 + mt], wf[bx][mt], b0, b1);
                if (bx + WO_PRE < 8) fetch(bx + WO_PRE);
            }
            float res[4];
#pragma unroll
            for (int i = 0; i < 4; i++) res[i] = pick(oa[i], lane) + pick(oa[4 + i], lane);
            if (__builtin_expect(fits(res[0]) && fits(res[1]) && fits(res[2]) && fits(res[3]), 1)) {
#pragma unroll
                for (int i = 0; i < 4; i++) red_add(oacc + 2 * i * ACC_S, to_fixed(res[i]) | 32);
            } else {
#pragma unroll
                for (int i = 0; i < 4; i++) add_silent(res[i], oacc + 2 * i * ACC_S);
            }
            if (lane == 0) asm volatile("mbarrier.arrive.relaxed.cta.shared::cta.b64 _, [%0];" ::"r"(sm + BAR_RED) : "memory");
#pragma unroll
            for (int i = 0; i < 4; i++) stg_rlx(P.gs + G_FIN + ksp * 2 * D_MODEL + e0 + 32 * i, tagf(res[i], tag));
            __syncwarp();
        }
        __nv_bfloat16* outp = P.out + oidx;
        uint32_t* finp = P.gs + G_FIN + (32 + ksd) * 2 * D_MODEL + elem;
        asm volatile("" : "+l"(outp), "+l"(finp));
        float da[4][4] = {};
        {
            uint32_t hf[28][2];
#pragma unroll
            for (int k = 0; k < 28; k++) {
                hf[k][0] = lds32(sm + SM_H + (g & 1) * HSTR + t * 4 + k * 32);
                hf[k][1] = lds32(sm + SM_H + (g & 1) * HSTR + t * 4 + k * 32 + 16);
            }
            const uint32_t ra = sm + SM_WD + ((j >> 1) * 8 + r) * 128 + (((2 * w + (j & 1)) ^ r) << 4);
            bool ready = false;
#pragma unroll
            for (int bx = 0; bx < 7; bx++) {
                if (!ready) mbar_wait(sm + BAR_WD + bx * 8, 0);
                if (bx < 6) ready = mbar_test(sm + BAR_WD + bx * 8 + 8, 0);
                uint32_t a[4][4];
#pragma unroll
                for (int i = 0; i < 4; i++) ldsm4t(ra + bx * 8192 + i * 2048, a[i]);
#pragma unroll
                for (int i = 0; i < 4; i++) mma(da[i], a[i], hf[bx * 4 + i][0], hf[bx * 4 + i][1]);
            }
        }
        const float res = (pick(da[0], lane) + pick(da[1], lane)) + (pick(da[2], lane) + pick(da[3], lane));
        unsigned long long q = to_fixed(res) | 1;
        asm volatile("" : "+l"(q));
        q = fits(res) ? q : 0;
        unsigned long long tot = atom_add(acc, q);
        stg_rlx(finp, tagf(res, tag));
        if (__builtin_expect(!fits(res), 0)) {
            flag_range(acc);
            tot = atom_add(acc, q = 1);
        }
        tot += q;
        const uint32_t lo = (uint32_t)tot;
        if ((lo & 0x1F) == NOWN) {
            const float sum = __ll2float_rn((long long)tot) * (1.f / FIX);
            asm volatile("{\n.reg .pred p;\nsetp.eq.u32 p, %1, %2;\n@p st.relaxed.gpu.global.L2::cache_hint.u64 [%0], 0, %3;\n}" ::"l"(acc),
                         "r"(lo & 0x7E0), "n"(NSIL << 5), "l"(NORMAL) : "memory");
            asm volatile("st.global.L2::cache_hint.u16 [%0], %1, %2;" ::"l"(outp), "h"(__bfloat16_as_ushort(__float2bfloat16_rn(sum))),
                         "l"(NORMAL) : "memory");
            if (__builtin_expect((lo & 0xFE0) != NSIL << 5 || tiny(sum, res), 0)) {
                *outp = __float2bfloat16_rn(finish_slow(P.gs, tot, elem, res, xres, tag));
                asm volatile("st.relaxed.gpu.global.u64 [%0], 0;" ::"l"(acc) : "memory");
            }
        }
    } else {
        const int w = warp - 5, tid = tx - 160;
        const uint32_t tag = launch_tag(P.gs + G_DONE + kvh * 32);
        asm volatile("cp.async.wait_all;\nfence.proxy.async.shared::cta;" ::: "memory");
        bar_sync(NB_INIT, NTHREADS);
        bar_sync(NB_QPUB, 256);
        if (lds32(sm + SM_META + 7 * 4) == 0) {
            const long long t0 = clock64();
            while (clock64() - t0 < Q_DELAY) {}
        }
#pragma unroll 1
        for (int b = 0; b < 2; b++) {
            const uint32_t* src = P.gs + G_Q + b * QW + kvh * 1024 + tid * 8;
            uint4 v0, v1;
            uint32_t spins = 0;
            while (true) {
                v0 = ldg_rlx4(src);
                v1 = ldg_rlx4(src + 4);
                if (__all_sync(~0u, ok4(v0, tag) && ok4(v1, tag))) break;
                if (++spins > SPIN_MAX) __trap();
                __nanosleep(100);
            }
            const uint32_t a = sm + SM_Q + (b * 8 + (tid >> 4)) * 272 + (tid & 15) * 16;
            sts64(a, pack_hi(v0.x, v0.y), pack_hi(v0.z, v0.w));
            sts64(a + 8, pack_hi(v1.x, v1.y), pack_hi(v1.z, v1.w));
            bar_arrive(b ? NB_Q1 : NB_Q0, 256);
        }
        if (!has_fin) return;
#pragma unroll 1
        for (int b = 0; b < 2; b++) {
            mbar_wait(sm + BAR_GO + b * 8, 0);
            if (b == 0) {
#pragma unroll 1
                for (int i = tid; i < HROWS / 2; i += 128) {
                    const int hb = i / (HROWS / 4), ch = i % (HROWS / 4);
                    const uint32_t* src = P.gs + G_H + hb * FF + ksd * HROWS + ch * 4;
                    uint4 v;
                    uint32_t spins = 0;
                    while (true) {
                        v = ldg_rlx4(src);
                        if (ok4(v, tag)) break;
                        if (++spins > SPIN_MAX) __trap();
                        __nanosleep(200);
                    }
                    sts64(sm + SM_H + hb * HSTR + ch * 8, pack_hi(v.x, v.y), pack_hi(v.z, v.w));
                }
                __syncwarp();
            }
            const int i4 = lane >> 3, j8 = lane & 7;
            const uint32_t* src = P.gs + G_PART + ((b * 32 + ksp) * MEMBERS + i4) * 128 + w * 32 + j8 * 4;
            const uint32_t* src32 = src + (32 - i4) * 128;
            const uint32_t* mls = P.gs + G_ML + ksp * 160 + 2 * b + lane * 4;
            const uint32_t* mls32 = mls + (32 - lane) * 4;
            asm volatile("" : "+l"(src), "+l"(src32), "+l"(mls), "+l"(mls32));
            if (b == 1) {
                if (tid == 0) {
                    const uint32_t target = tag * MEMBERS % (15 * MEMBERS);
                    uint32_t spins = 0;
                    while (ldg_rlx(P.gs + G_DONE + kvh * 32) != target && ++spins < 256) {}
                    mbar_arrive(sm + BAR_COMB);
                }
                __syncwarp();
                bar_sync(NB_AUX, 128);
            }
            uint32_t o01, o23;
            auto attempt = [&]() {
                uint4 v[9];
                const uint2 ml = ldg_rlx2(mls), ml32 = ldg_rlx2(mls32);
#pragma unroll
                for (int n = 0; n < 8; n++) v[n] = ldg_rlx4(src + n * 512);
                v[8] = ldg_rlx4(src32);
                const int mo = __reduce_max_sync(~0u, (int)(ml.x ^ (((int)ml.x >> 31) & 0x7FFFFFFF)));
                const float M = fmaxf(untag(mo ^ ((mo >> 31) & 0x7FFFFFFF)), untag(ml32.x));
                const float e = expd(untag(ml.x) - M), e32 = expd(untag(ml32.x) - M);
                float en[8];
#pragma unroll
                for (int n = 0; n < 8; n++) en[n] = __shfl_sync(~0u, e, i4 + 4 * n);
                float L = e * untag(ml.y);
#pragma unroll
                for (int s = 16; s; s >>= 1) L += __shfl_xor_sync(~0u, L, s);
                const float inv = __frcp_rn(fmaf(e32, untag(ml32.y), L));
                uint32_t bad[4] = {ml.x ^ tag, ml.y ^ tag, ml32.x ^ tag, ml32.y ^ tag};
                float a0 = 0.f, a1 = 0.f, a2 = 0.f, a3 = 0.f;
#pragma unroll
                for (int n = 0; n < 9; n++) {
                    or_xor(bad[0], v[n].x, tag); or_xor(bad[1], v[n].y, tag); or_xor(bad[2], v[n].z, tag); or_xor(bad[3], v[n].w, tag);
                    if (n < 8) {
                        a0 = fmaf(en[n], untag(v[n].x), a0); a1 = fmaf(en[n], untag(v[n].y), a1);
                        a2 = fmaf(en[n], untag(v[n].z), a2); a3 = fmaf(en[n], untag(v[n].w), a3);
                    }
                }
#pragma unroll
                for (int s = 8; s < 32; s <<= 1) {
                    a0 += __shfl_xor_sync(~0u, a0, s);
                    a1 += __shfl_xor_sync(~0u, a1, s);
                    a2 += __shfl_xor_sync(~0u, a2, s);
                    a3 += __shfl_xor_sync(~0u, a3, s);
                }
                o01 = pack_bf16(fmaf(e32, untag(v[8].x), a0) * inv, fmaf(e32, untag(v[8].y), a1) * inv);
                o23 = pack_bf16(fmaf(e32, untag(v[8].z), a2) * inv, fmaf(e32, untag(v[8].w), a3) * inv);
                return __all_sync(~0u, (((bad[0] | bad[1]) | (bad[2] | bad[3])) & 0xF) == 0);
            };
            if (__builtin_expect(!attempt(), 0)) {
                uint32_t spins = 0;
                while (!attempt())
                    if (++spins > SPIN_MAX) __trap();
            }
            if (i4 == 0) sts64(sm + SM_O + b * 272 + (w * 32 + j8 * 4) * 2, o01, o23);
        }
        bar_arrive(NB_O, 256);
        if (member == 0 && tid == 0)
            red_add(reinterpret_cast<unsigned long long*>(P.gs + G_CTR), 0ull - ((unsigned long long)TILES << (16 * kvh)));
    }
}

typedef CUresult (*EncodeFn)(CUtensorMap*, CUtensorMapDataType, cuuint32_t, void*, const cuuint64_t*, const cuuint64_t*,
                             const cuuint32_t*, const cuuint32_t*, CUtensorMapInterleave, CUtensorMapSwizzle,
                             CUtensorMapL2promotion, CUtensorMapFloatOOBfill);

void make_map(EncodeFn enc, CUtensorMap* m, const void* p, uint64_t d0, uint64_t d1, uint64_t d2, uint64_t s1, uint64_t s2,
              uint32_t b0, uint32_t b1, uint32_t b2, CUtensorMapSwizzle sw, CUtensorMapL2promotion pr) {
    cuuint64_t d[3] = {d0, d1, d2}, s[2] = {s1, s2};
    cuuint32_t b[3] = {b0, b1, b2}, e[3] = {1, 1, 1};
    enc(m, CU_TENSOR_MAP_DATA_TYPE_BFLOAT16, 3, const_cast<void*>(p), d, s, b, e, CU_TENSOR_MAP_INTERLEAVE_NONE, sw, pr,
        CU_TENSOR_MAP_FLOAT_OOB_FILL_NONE);
}

}

extern "C" void kernel_launch(void* const* d_in, const int* in_sizes, int n_in, void* d_out, int out_size) {
    void* fn = nullptr;
    cudaDriverEntryPointQueryResult qr;
    cudaGetDriverEntryPoint("cuTensorMapEncodeTiled", &fn, cudaEnableDefault, &qr);
    EncodeFn enc = (EncodeFn)fn;
    Params P;
    const CUtensorMapL2promotion p128 = CU_TENSOR_MAP_L2_PROMOTION_L2_128B, p256 = CU_TENSOR_MAP_L2_PROMOTION_L2_256B;
    make_map(enc, &P.k, d_in[1], 64, 8 * SK, 2, 256, 128, 64, 64, 2, CU_TENSOR_MAP_SWIZZLE_128B, p256);
    make_map(enc, &P.v, d_in[2], 64, 8 * SK, 2, 256, 128, 64, 64, 2, CU_TENSOR_MAP_SWIZZLE_128B, p256);
    make_map(enc, &P.wq, d_in[3], QW, D_MODEL, 1, QW * 2, (uint64_t)QW * 2 * D_MODEL, 32, 256, 1, CU_TENSOR_MAP_SWIZZLE_64B, p128);
    make_map(enc, &P.wg, d_in[6], FF, D_MODEL, 1, FF * 2, (uint64_t)FF * 2 * D_MODEL, 32, 256, 1, CU_TENSOR_MAP_SWIZZLE_64B, p128);
    make_map(enc, &P.wu, d_in[7], FF, D_MODEL, 1, FF * 2, (uint64_t)FF * 2 * D_MODEL, 32, 256, 1, CU_TENSOR_MAP_SWIZZLE_64B, p128);
    make_map(enc, &P.wo, d_in[4], 64, QW, 16, 2048, 128, 64, 16, 4, CU_TENSOR_MAP_SWIZZLE_128B, p256);
    make_map(enc, &P.wd, d_in[8], 64, FF, 16, 2048, 128, 64, 64, 1, CU_TENSOR_MAP_SWIZZLE_128B, p256);
    P.x = (const __nv_bfloat16*)d_in[0];
    P.wq_raw = (const char*)d_in[3];
    P.wg_raw = (const char*)d_in[6] - GU_FIRST * 64;
    P.out = (__nv_bfloat16*)d_out;
    cudaGetSymbolAddress((void**)&P.gs, g_s);
    cudaFuncSetAttribute(fused_decode_kernel, cudaFuncAttributeMaxDynamicSharedMemorySize, SM_TOTAL);
    cudaLaunchAttribute attr;
    attr.id = cudaLaunchAttributeCooperative;
    attr.val.cooperative = 1;
    cudaLaunchConfig_t cfg = {};
    cfg.gridDim = dim3(NCTA);
    cfg.blockDim = dim3(NTHREADS);
    cfg.dynamicSmemBytes = SM_TOTAL;
    cfg.stream = cudaStreamPerThread;
    cfg.attrs = &attr;
    cfg.numAttrs = 1;
    cudaLaunchKernelEx(&cfg, fused_decode_kernel, P);
}
```
